```python
import torch

def _softmax(x, axis=-1):
    return torch.softmax(x, dim=axis)

def _gelu(x):
    return torch.nn.functional.gelu(x, approximate='tanh')

def _silu(x):
    return torch.nn.functional.silu(x)

def _sigmoid(x):
    return torch.sigmoid(x)

def _layernorm(x, axis=-1, eps=1e-05):
    m = x.mean(dim=axis, keepdim=True)
    v = x.var(dim=axis, keepdim=True, unbiased=False)
    return (x - m) / torch.sqrt(v + eps)

def _scatter_add(tgt, idx, src, axis=0):
    return tgt.clone().index_add_(axis, idx, src)

def _segment_sum(src, seg, n):
    out = torch.zeros((n,) + src.shape[1:], dtype=src.dtype)
    return out.index_add_(0, seg, src)

def _pad(x, pw):
    flat = tuple((v for pair in reversed(pw) for v in pair))
    return torch.nn.functional.pad(x, flat)
kernel_name = 'adaLN_cond__gqa_block_cached__swiglu_ffn__prompt'

def setup_inputs():

    _w = lambda a: (lambda t: t.to(torch.bfloat16) if t.is_floating_point() else t)(torch.as_tensor(a))

    def _A_setup():
        B, Sq, D = (1, 2048, 512)
        Hq, Hkv, Sk, Dh = (32, 8, 2048, 128)
        assert Hq % Hkv == 0, (Hq, Hkv)
        return {'x': _w((lambda *s: torch.randn(*s, dtype=torch.bfloat16) * 0.05)(B, Sq, D)), 'k_cache': _w((lambda *s: torch.randn(*s, dtype=torch.bfloat16) * 3.2)(B, Hkv, Sk, Dh)), 'v_cache': _w((lambda *s: torch.randn(*s, dtype=torch.bfloat16) * 0.4)(B, Hkv, Sk, Dh)), 'wq': _w((lambda *s: torch.randn(*s, dtype=torch.bfloat16) * 3.2)(D, Hq * Dh) * D ** (-0.5)), 'wo': _w((lambda *s: torch.randn(*s, dtype=torch.bfloat16) * 0.4)(Hq * Dh, D) * (Hq * Dh) ** (-0.5))}
    _A_in = _A_setup()

    def _B_setup():
        B, S, D, F = (1, 2048, 512, 1792)
        return {'x': _w((lambda *s: torch.randn(*s, dtype=torch.bfloat16) * 0.05)(B, S, D)), 'w_gate': _w((lambda *s: torch.randn(*s, dtype=torch.bfloat16) * 0.05)(D, F)), 'w_up': _w((lambda *s: torch.randn(*s, dtype=torch.bfloat16) * 0.05)(D, F)), 'w_down': _w((lambda *s: torch.randn(*s, dtype=torch.bfloat16) * 0.05)(F, D))}
    _B_in = _B_setup()
    return {'A_x': _A_in['x'], 'A_k_cache': _A_in['k_cache'], 'A_v_cache': _A_in['v_cache'], 'A_wq': _A_in['wq'], 'A_wo': _A_in['wo'], 'B_x': _B_in['x'], 'B_w_gate': _B_in['w_gate'], 'B_w_up': _B_in['w_up'], 'B_w_down': _B_in['w_down'], 'c': _w((lambda *s: torch.randn(*s, dtype=torch.bfloat16) * 0.1)(1, 512) * 8.0), 'w_mod': _w((lambda *s: torch.randn(*s, dtype=torch.bfloat16) * 0.1)(512, 6 * 512) * 512 ** (-0.5) * 8.0)}

def reference(A_x, A_k_cache, A_v_cache, A_wq, A_wo, B_x, B_w_gate, B_w_up, B_w_down, c, w_mod):

    def _A_ref(x, k_cache, v_cache, wq, wo):
        B, Sq, D = x.shape
        Hq, Dh = (32, 128)
        Hkv = k_cache.shape[1]
        rep = Hq // Hkv
        q = (lambda x, *d: x.permute(*d))((x @ wq).reshape(B, Sq, Hq, Dh), 0, 2, 1, 3)
        k = (lambda x, n, axis: torch.repeat_interleave(x, n, dim=axis))(k_cache, rep, axis=1)
        v = (lambda x, n, axis: torch.repeat_interleave(x, n, dim=axis))(v_cache, rep, axis=1)
        scores = torch.einsum('bhqd,bhkd->bhqk', q, k) * Dh ** (-0.5)
        p = _softmax(scores, axis=-1)
        o = torch.einsum('bhqk,bhkd->bhqd', p, v)
        return (lambda x, *d: x.permute(*d))(o, 0, 2, 1, 3).reshape(B, Sq, Hq * Dh) @ wo

    def _B_ref(x, w_gate, w_up, w_down):
        g = _silu(x @ w_gate)
        u = x @ w_up
        return g * u @ w_down
    x = A_x
    mod = (_silu(c) @ w_mod).reshape(c.shape[0], 6, 1, -1)
    sa, ca, ga, sb, cb, gb = (mod[:, 0].clone(), mod[:, 1].clone(), mod[:, 2].clone(), mod[:, 3].clone(), mod[:, 4].clone(), mod[:, 5].clone())
    h = _layernorm(x, axis=-1) * (1 + ca) + sa
    x = x + ga * _A_ref(h, A_k_cache, A_v_cache, A_wq, A_wo)
    h = _layernorm(x, axis=-1) * (1 + cb) + sb
    x = x + gb * _B_ref(h, B_w_gate, B_w_up, B_w_down)
    return x
```

```cpp
#include <cuda_runtime.h>
#include <cuda_bf16.h>
#include <cuda.h>
#include <stdint.h>

namespace {

constexpr int NS = 6;
constexpr int SLOT = 32768;
constexpr int OFF_BAR = NS * SLOT;
constexpr int OFF_LN1 = OFF_BAR + 128;
constexpr int OFF_LN2 = OFF_LN1 + 4096;
constexpr int OFF_GA = OFF_LN2 + 4096;
constexpr int OFF_GB = OFF_GA + 2048;
constexpr int OFF_RED = OFF_GB + 2048;
constexpr int SMEM_BYTES = OFF_RED + 1024;

constexpr int BAR_PP = 1;
constexpr int BAR_SOLO = 3;
constexpr int BAR_WG = 5;
constexpr int BAR_CONS = 7;

enum { CNT_INIT = 0, CNT_O = 1, CNT_READ = 2, CNT_D = 3 };

__device__ uint32_t g_epoch;
__device__ uint32_t g_mod[3072];
__device__ uint32_t g_cnt[4 * 32 * 32];
__device__ uint4 g_stash[128 * 24 * 256];
__device__ float4 g_xacc[32 * 64 * 128];

template<int TRANSB> __device__ __forceinline__ void wgmma_n128(float (&d)[64], uint32_t a0, uint32_t a1, uint32_t a2, uint32_t a3, uint64_t descB, int scaleD) {
  asm volatile("{\n.reg .pred p;\n"
    "setp.ne.b32 p, %69, 0;\n"
    "wgmma.mma_async.sync.aligned.m64n128k16.f32.bf16.bf16 "
    "{%0, %1, %2, %3, %4, %5, %6, %7, %8, %9, %10, %11, %12, %13, %14, %15, "
    "%16, %17, %18, %19, %20, %21, %22, %23, %24, %25, %26, %27, %28, %29, %30, %31, "
    "%32, %33, %34, %35, %36, %37, %38, %39, %40, %41, %42, %43, %44, %45, %46, %47, "
    "%48, %49, %50, %51, %52, %53, %54, %55, %56, %57, %58, %59, %60, %61, %62, %63}, "
    "{%64, %65, %66, %67}, %68, p, 1, 1, %70;\n}\n"
    : "+f"(d[0]), "+f"(d[1]), "+f"(d[2]), "+f"(d[3]), "+f"(d[4]), "+f"(d[5]), "+f"(d[6]), "+f"(d[7]),
      "+f"(d[8]), "+f"(d[9]), "+f"(d[10]), "+f"(d[11]), "+f"(d[12]), "+f"(d[13]), "+f"(d[14]), "+f"(d[15]),
      "+f"(d[16]), "+f"(d[17]), "+f"(d[18]), "+f"(d[19]), "+f"(d[20]), "+f"(d[21]), "+f"(d[22]), "+f"(d[23]),
      "+f"(d[24]), "+f"(d[25]), "+f"(d[26]), "+f"(d[27]), "+f"(d[28]), "+f"(d[29]), "+f"(d[30]), "+f"(d[31]),
      "+f"(d[32]), "+f"(d[33]), "+f"(d[34]), "+f"(d[35]), "+f"(d[36]), "+f"(d[37]), "+f"(d[38]), "+f"(d[39]),
      "+f"(d[40]), "+f"(d[41]), "+f"(d[42]), "+f"(d[43]), "+f"(d[44]), "+f"(d[45]), "+f"(d[46]), "+f"(d[47]),
      "+f"(d[48]), "+f"(d[49]), "+f"(d[50]), "+f"(d[51]), "+f"(d[52]), "+f"(d[53]), "+f"(d[54]), "+f"(d[55]),
      "+f"(d[56]), "+f"(d[57]), "+f"(d[58]), "+f"(d[59]), "+f"(d[60]), "+f"(d[61]), "+f"(d[62]), "+f"(d[63])
    : "r"(a0), "r"(a1), "r"(a2), "r"(a3), "l"(descB), "r"(scaleD), "n"(TRANSB));
}
template<int TRANSB> __device__ __forceinline__ void wgmma_n64(float (&d)[32], uint32_t a0, uint32_t a1, uint32_t a2, uint32_t a3, uint64_t descB, int scaleD) {
  asm volatile("{\n.reg .pred p;\n"
    "setp.ne.b32 p, %37, 0;\n"
    "wgmma.mma_async.sync.aligned.m64n64k16.f32.bf16.bf16 "
    "{%0, %1, %2, %3, %4, %5, %6, %7, %8, %9, %10, %11, %12, %13, %14, %15, "
    "%16, %17, %18, %19, %20, %21, %22, %23, %24, %25, %26, %27, %28, %29, %30, %31}, "
    "{%32, %33, %34, %35}, %36, p, 1, 1, %38;\n}\n"
    : "+f"(d[0]), "+f"(d[1]), "+f"(d[2]), "+f"(d[3]), "+f"(d[4]), "+f"(d[5]), "+f"(d[6]), "+f"(d[7]),
      "+f"(d[8]), "+f"(d[9]), "+f"(d[10]), "+f"(d[11]), "+f"(d[12]), "+f"(d[13]), "+f"(d[14]), "+f"(d[15]),
      "+f"(d[16]), "+f"(d[17]), "+f"(d[18]), "+f"(d[19]), "+f"(d[20]), "+f"(d[21]), "+f"(d[22]), "+f"(d[23]),
      "+f"(d[24]), "+f"(d[25]), "+f"(d[26]), "+f"(d[27]), "+f"(d[28]), "+f"(d[29]), "+f"(d[30]), "+f"(d[31])
    : "r"(a0), "r"(a1), "r"(a2), "r"(a3), "l"(descB), "r"(scaleD), "n"(TRANSB));
}

__device__ __forceinline__ uint32_t smem_u32(const void* p) { return (uint32_t)__cvta_generic_to_shared(p); }
__device__ __forceinline__ void wg_fence() { asm volatile("wgmma.fence.sync.aligned;" ::: "memory"); }
__device__ __forceinline__ void wg_commit() { asm volatile("wgmma.commit_group.sync.aligned;" ::: "memory"); }
template<int N> __device__ __forceinline__ void wg_wait() { asm volatile("wgmma.wait_group.sync.aligned %0;" :: "n"(N) : "memory"); }
template<int N> __device__ __forceinline__ void fence_regs(float (&d)[N]) {
#pragma unroll
  for (int i = 0; i < N; i++) asm volatile("" : "+f"(d[i]) :: "memory");
}
template<int N> __device__ __forceinline__ void fence_regs(uint32_t (&d)[N]) {
#pragma unroll
  for (int i = 0; i < N; i++) asm volatile("" : "+r"(d[i]) :: "memory");
}
__device__ __forceinline__ void sched_fence() { asm volatile("pmevent 0;" ::: "memory"); }
__device__ __forceinline__ void mbar_init(uint32_t bar, uint32_t cnt) { asm volatile("mbarrier.init.shared::cta.b64 [%0], %1;" :: "r"(bar), "r"(cnt) : "memory"); }
__device__ __forceinline__ void mbar_expect_tx(uint32_t bar, uint32_t bytes) { asm volatile("mbarrier.arrive.expect_tx.shared::cta.b64 _, [%0], %1;" :: "r"(bar), "r"(bytes) : "memory"); }
__device__ __forceinline__ void mbar_wait(uint32_t bar, uint32_t parity) {
  asm volatile("{\n.reg .pred p;\n.reg .u32 it;\nmov.u32 it, 0;\n"
    "LAB_WAIT:\n"
    "mbarrier.try_wait.parity.shared::cta.b64 p, [%0], %1;\n"
    "@p bra LAB_DONE;\n"
    "add.u32 it, it, 1;\n"
    "setp.lt.u32 p, it, 2000000;\n"
    "@p bra LAB_WAIT;\n"
    "trap;\n"
    "LAB_DONE:\n}" :: "r"(bar), "r"(parity) : "memory");
}
__device__ __forceinline__ void flag_wait(const uint32_t* p, uint32_t target) {
  asm volatile("{\n.reg .pred p;\n.reg .u32 it, v;\nmov.u32 it, 0;\n"
    "LAB_WAIT:\n"
    "ld.acquire.gpu.global.u32 v, [%0];\n"
    "sub.u32 v, v, %1;\n"
    "setp.ge.s32 p, v, 0;\n"
    "@p bra LAB_DONE;\n"
    "add.u32 it, it, 1;\n"
    "setp.lt.u32 p, it, 4000000;\n"
    "@p bra LAB_WAIT;\n"
    "trap;\n"
    "LAB_DONE:\n}" :: "l"(p), "r"(target) : "memory");
}
__device__ __forceinline__ void flag_arrive(uint32_t* p) { asm volatile("fence.acq_rel.gpu;\nred.relaxed.gpu.global.add.u32 [%0], 1;" :: "l"(p) : "memory"); }
__device__ __forceinline__ uint4 tagged_wait(const uint32_t* p, uint32_t tag) {
  uint4 v;
  asm volatile("{\n.reg .pred p;\n.reg .u32 it, a, b;\nmov.u32 it, 0;\n"
    "LAB_WAIT:\n"
    "ld.relaxed.gpu.global.v4.u32 {%0, %1, %2, %3}, [%4];\n"
    "xor.b32 a, %0, %5;\n xor.b32 b, %1, %5;\n or.b32 a, a, b;\n xor.b32 b, %2, %5;\n or.b32 a, a, b;\n xor.b32 b, %3, %5;\n or.b32 a, a, b;\n"
    "setp.lt.u32 p, a, 65536;\n"
    "@p bra LAB_DONE;\n"
    "add.u32 it, it, 1;\n"
    "setp.lt.u32 p, it, 4000000;\n"
    "@p bra LAB_WAIT;\n"
    "trap;\n"
    "LAB_DONE:\n}" : "=&r"(v.x), "=&r"(v.y), "=&r"(v.z), "=&r"(v.w) : "l"(p), "r"(tag << 16) : "memory");
  return v;
}
__device__ __forceinline__ void tma_load(uint32_t dst, const CUtensorMap* m, uint32_t bar, int c0, int c1) {
  asm volatile("cp.async.bulk.tensor.2d.shared::cluster.global.mbarrier::complete_tx::bytes [%0], [%1, {%3, %4}], [%2];"
    :: "r"(dst), "l"(m), "r"(bar), "r"(c0), "r"(c1) : "memory");
}
__device__ __forceinline__ void tma_load_mc(uint32_t dst, const CUtensorMap* m, uint32_t bar, int c0, int c1) {
  asm volatile("cp.async.bulk.tensor.2d.shared::cluster.global.mbarrier::complete_tx::bytes.multicast::cluster [%0], [%1, {%3, %4}], [%2], %5;"
    :: "r"(dst), "l"(m), "r"(bar), "r"(c0), "r"(c1), "h"((uint16_t)3) : "memory");
}
__device__ __forceinline__ void cluster_sync() { asm volatile("barrier.cluster.arrive.release.aligned;\nbarrier.cluster.wait.acquire.aligned;" ::: "memory"); }
__device__ __forceinline__ void bar_sync(int id, int n) { asm volatile("bar.sync %0, %1;" :: "r"(id), "r"(n) : "memory"); }
__device__ __forceinline__ void bar_arrive(int id, int n) { asm volatile("bar.arrive %0, %1;" :: "r"(id), "r"(n) : "memory"); }
__device__ __forceinline__ float ex2(float x) { float y; asm("ex2.approx.ftz.f32 %0, %1;" : "=f"(y) : "f"(x)); return y; }
__device__ __forceinline__ float rcp(float x) { float y; asm("rcp.approx.ftz.f32 %0, %1;" : "=f"(y) : "f"(x)); return y; }
__device__ __forceinline__ uint32_t pack_bf16(float lo, float hi) { uint32_t r; asm("cvt.rn.bf16x2.f32 %0, %1, %2;" : "=r"(r) : "f"(hi), "f"(lo)); return r; }
__device__ __forceinline__ float bf_lo(uint32_t v) { return __uint_as_float(v << 16); }
__device__ __forceinline__ float bf_hi(uint32_t v) { return __uint_as_float(v & 0xffff0000u); }
__device__ __forceinline__ float bf_round(float x) { return bf_lo(pack_bf16(x, 0.f)); }
__device__ __forceinline__ uint64_t desc_from(uint32_t lo, uint32_t hi) { uint64_t d; asm("mov.b64 %0, {%1, %2};" : "=l"(d) : "r"(lo), "r"(hi)); return d; }
__device__ __forceinline__ float4 lds128(uint32_t a) { float4 v; asm volatile("ld.shared.v4.f32 {%0,%1,%2,%3}, [%4];" : "=f"(v.x), "=f"(v.y), "=f"(v.z), "=f"(v.w) : "r"(a)); return v; }
__device__ __forceinline__ float2 lds64(uint32_t a) { float2 v; asm volatile("ld.shared.v2.f32 {%0,%1}, [%2];" : "=f"(v.x), "=f"(v.y) : "r"(a)); return v; }
__device__ __forceinline__ void sts32(uint32_t a, float v) { asm volatile("st.shared.f32 [%0], %1;" :: "r"(a), "f"(v) : "memory"); }
__device__ __forceinline__ void ldsm4(uint32_t a, uint32_t& r0, uint32_t& r1, uint32_t& r2, uint32_t& r3) {
  asm volatile("ldmatrix.sync.aligned.m8n8.x4.shared.b16 {%0,%1,%2,%3}, [%4];" : "=r"(r0), "=r"(r1), "=r"(r2), "=r"(r3) : "r"(a) : "memory");
}
__device__ __forceinline__ void red128(float4* p, float a, float b, float c, float d) {
  asm volatile("red.relaxed.gpu.global.add.v4.f32 [%0], {%1,%2,%3,%4};" :: "l"(p), "f"(a), "f"(b), "f"(c), "f"(d) : "memory");
}
__device__ __forceinline__ float silu_f(float v) { return v * rcp(1.f + ex2(v * -1.4426950408889634f)); }

constexpr uint32_t HI_SW128 = (1024 >> 4) | (1u << 30);
constexpr uint32_t HI_SW64 = (512 >> 4) | (2u << 30);
constexpr uint32_t LBO_BOX = (16384u >> 4) << 16;

#define STAMP(i)

struct Maps { CUtensorMap x, wq, k, v, wo, wg, wu, wd; };

__device__ __forceinline__ void ln_apply(uint32_t (&a)[128], float s0, float q0, float s1, float q1, uint32_t prm) {
  s0 += __shfl_xor_sync(0xffffffff, s0, 1); q0 += __shfl_xor_sync(0xffffffff, q0, 1);
  s1 += __shfl_xor_sync(0xffffffff, s1, 1); q1 += __shfl_xor_sync(0xffffffff, q1, 1);
  s0 += __shfl_xor_sync(0xffffffff, s0, 2); q0 += __shfl_xor_sync(0xffffffff, q0, 2);
  s1 += __shfl_xor_sync(0xffffffff, s1, 2); q1 += __shfl_xor_sync(0xffffffff, q1, 2);
  const float m0 = s0 * (1.f / 512), m1 = s1 * (1.f / 512);
  const float r0 = rsqrtf(fmaxf(q0 * (1.f / 512) - m0 * m0, 0.f) + 1e-5f), r1 = rsqrtf(fmaxf(q1 * (1.f / 512) - m1 * m1, 0.f) + 1e-5f);
  const float b0 = -m0 * r0, b1 = -m1 * r1;
  fence_regs(a);
#pragma unroll
  for (int kk = 0; kk < 32; kk++) {
    if (kk % 4 == 0) sched_fence();
    const float4 c = lds128(prm + kk * 128), s = lds128(prm + kk * 128 + 64);
    a[4*kk]   = pack_bf16(fmaf(fmaf(bf_lo(a[4*kk]),   r0, b0), c.x, s.x), fmaf(fmaf(bf_hi(a[4*kk]),   r0, b0), c.y, s.y));
    a[4*kk+1] = pack_bf16(fmaf(fmaf(bf_lo(a[4*kk+1]), r1, b1), c.x, s.x), fmaf(fmaf(bf_hi(a[4*kk+1]), r1, b1), c.y, s.y));
    a[4*kk+2] = pack_bf16(fmaf(fmaf(bf_lo(a[4*kk+2]), r0, b0), c.z, s.z), fmaf(fmaf(bf_hi(a[4*kk+2]), r0, b0), c.w, s.w));
    a[4*kk+3] = pack_bf16(fmaf(fmaf(bf_lo(a[4*kk+3]), r1, b1), c.z, s.z), fmaf(fmaf(bf_hi(a[4*kk+3]), r1, b1), c.w, s.w));
  }
}

__global__ void __launch_bounds__(384, 1)
block_kernel(const __grid_constant__ Maps maps, const __nv_bfloat16* __restrict__ cvec, const uint4* __restrict__ wmod,
             uint32_t* __restrict__ out) {
  extern __shared__ __align__(1024) uint8_t smem_raw[];
  const uint32_t sb = smem_u32(smem_raw);
  const uint32_t bfull = sb + OFF_BAR, bempty = bfull + 64;
  uint32_t rank; asm("mov.u32 %0, %%cluster_ctarank;" : "=r"(rank));
  const int wg = __shfl_sync(0xffffffff, threadIdx.x / 128, 0);
  const int hg = (blockIdx.x >> 1) & 7;
  const int rb = (blockIdx.x >> 4) * 2 + rank;
  if (threadIdx.x == 0) {
    for (int i = 0; i < NS; i++) { mbar_init(bfull + i*8, 1); mbar_init(bempty + i*8, 4); }
    asm volatile("fence.mbarrier_init.release.cluster;" ::: "memory");
  }
  __syncthreads();
  cluster_sync();

  if (wg == 0) {
    asm volatile("setmaxnreg.dec.sync.aligned.u32 24;");
    const int warp = __shfl_sync(0xffffffff, threadIdx.x / 32, 0);
    if (warp == 0) {
      if (threadIdx.x == 0) {
        uint32_t slot = 0, phase = 1;
        auto acquire = [&](uint32_t bytes) { mbar_wait(bempty + slot*8, phase); mbar_expect_tx(bfull + slot*8, bytes); };
        auto advance = [&]() { if (++slot == NS) { slot = 0; phase ^= 1; } };
        auto load = [&](const CUtensorMap* m, int c0, int c1, uint32_t bytes) {
          acquire(bytes);
          tma_load_mc(sb + slot*SLOT + rank*16384, m, bfull + slot*8, c0, c1);
          advance();
        };
        _Pragma("unroll 1") for (int t = 0; t < 4; t++) {
          acquire(SLOT);
          tma_load(sb + slot*SLOT, &maps.x, bfull + slot*8, t*128, rb*128);
          tma_load(sb + slot*SLOT + 16384, &maps.x, bfull + slot*8, t*128 + 64, rb*128);
          advance();
        }
        _Pragma("unroll 1") for (int t = 0; t < 16; t++) load(&maps.wq, (hg*4 + (((t >> 2) + 1) & 3))*128 + rank*64, (t & 3)*128, SLOT);
        load(&maps.k, rank*64, hg*2048, SLOT);
        _Pragma("unroll 1") for (int it = 1; it < 64; it++) {
          load(&maps.k, rank*64, hg*2048 + (it & 15)*128, SLOT);
          load(&maps.v, rank*64, hg*2048 + ((it-1) & 15)*128, SLOT);
        }
        load(&maps.v, rank*64, hg*2048 + 15*128, SLOT);
        _Pragma("unroll 1") for (int t = 0; t < 16; t++) load(&maps.wo, (((t >> 1) + hg) & 7)*64, hg*512 + (t & 1)*256 + rank*128, SLOT);
        _Pragma("unroll 1") for (int t = 0; t < 14; t++) load(rank ? &maps.wu : &maps.wg, hg*224 + (t >> 1)*32, (t & 1)*256, SLOT);
        _Pragma("unroll 1") for (int t = 0; t < 8; t++) load(&maps.wd, ((t + hg) & 7)*64, hg*224 + rank*112, 28672);
      }
    } else if (warp <= 2) {
      const int cw = warp - 1;
      const int lane = threadIdx.x & 31;
      uint32_t rbar; asm("mapa.shared::cluster.u32 %0, %1, %2;" : "=r"(rbar) : "r"(bempty), "r"(lane & 1));
      uint32_t slot = 0, phase = 0, rel = 0;
      auto wait_full = [&]() { mbar_wait(bfull + slot*8, phase); if (++slot == NS) { slot = 0; phase ^= 1; } };
      auto release = [&]() {
        if (lane < 2) asm volatile("mbarrier.arrive.shared::cluster.b64 _, [%0];" :: "r"(rbar + rel*8) : "memory");
        if (++rel == NS) rel = 0;
      };
      _Pragma("unroll 1") for (int t = 0; t < 4; t++) wait_full();
      bar_sync(BAR_SOLO + cw, 160);
      bar_sync(BAR_SOLO + cw, 160);
      _Pragma("unroll 1") for (int t = 0; t < 4; t++) release();
      int prev = 0;
      _Pragma("unroll 1") for (int st = 0; st < 16 + 65 + 38; st++) {
        const int n = (st > 16 && st < 16 + 64) ? 2 : 1;
        wait_full(); if (n == 2) wait_full();
        bar_sync(BAR_PP + cw, 288);
        if (prev >= 1) release(); if (prev == 2) release();
        prev = n;
      }
    }
    __syncwarp();
    cluster_sync();
  } else {
    asm volatile("setmaxnreg.inc.sync.aligned.u32 240;");
    const int cw = wg - 1;
    const int tid = threadIdx.x - 128, lane = threadIdx.x & 31, t4 = lane & 3;
    const uint32_t sbm = sb & 0x3FFFF;
    STAMP(0);
    uint32_t epoch; asm volatile("ld.relaxed.gpu.global.u32 %0, [%1];" : "=r"(epoch) : "l"(&g_epoch) : "memory");
    uint4* const stash = g_stash + (size_t)blockIdx.x * 24 * 256 + tid;
    float4* const xacc = g_xacc + (size_t)(rb * 2 + cw) * 64 * 128 + (tid & 127);
    uint32_t* const cnt = g_cnt + (rb * 2 + cw) * 32;
    uint32_t slot = 4;
    auto nxt = [&]() { const uint32_t s_ = slot; slot = (slot == NS - 1) ? 0 : slot + 1; return (sbm + s_ * SLOT) >> 4; };
    auto pp_enter = [&]() { bar_sync(BAR_PP + cw, 288); };
    auto pp_leave = [&]() { bar_arrive(BAR_PP + (cw ^ 1), 288); sched_fence(); };

    {
      uint4 w[6];
#pragma unroll
      for (int i = 0; i < 6; i++) w[i] = __ldg(wmod + (size_t)(tid + (i / 3) * 256) * 384 + blockIdx.x * 3 + (i % 3));
      const float c0 = bf_round(silu_f(__bfloat162float(cvec[tid]))), c1 = bf_round(silu_f(__bfloat162float(cvec[tid + 256])));
      float v[24];
#pragma unroll
      for (int i = 0; i < 3; i++) {
        const uint32_t x[4] = {w[i].x, w[i].y, w[i].z, w[i].w}, y[4] = {w[3+i].x, w[3+i].y, w[3+i].z, w[3+i].w};
#pragma unroll
        for (int e = 0; e < 4; e++) { v[8*i+2*e] = fmaf(c0, bf_lo(x[e]), c1 * bf_lo(y[e])); v[8*i+2*e+1] = fmaf(c0, bf_hi(x[e]), c1 * bf_hi(y[e])); }
      }
#pragma unroll
      for (int i = 0; i < 12; i++) { const bool up = lane & 16; const float snd = up ? v[i] : v[i+12], keep = up ? v[i+12] : v[i]; v[i] = keep + __shfl_xor_sync(0xffffffff, snd, 16); }
#pragma unroll
      for (int i = 0; i < 6; i++) { const bool up = lane & 8; const float snd = up ? v[i] : v[i+6], keep = up ? v[i+6] : v[i]; v[i] = keep + __shfl_xor_sync(0xffffffff, snd, 8); }
#pragma unroll
      for (int i = 0; i < 3; i++) { const bool up = lane & 4; const float snd = up ? v[i] : v[i+3], keep = up ? v[i+3] : v[i]; v[i] = keep + __shfl_xor_sync(0xffffffff, snd, 4); }
#pragma unroll
      for (int i = 0; i < 3; i++) { v[i] += __shfl_xor_sync(0xffffffff, v[i], 2); v[i] += __shfl_xor_sync(0xffffffff, v[i], 1); }
      if (t4 < 3) {
        const int col = ((lane >> 4) & 1) * 12 + ((lane >> 3) & 1) * 6 + ((lane >> 2) & 1) * 3 + t4;
        sts32(sb + OFF_RED + ((tid >> 5) * 24 + col) * 4, t4 == 0 ? v[0] : t4 == 1 ? v[1] : v[2]);
      }
      bar_sync(BAR_CONS, 256);
      if (tid < 24) {
        float s = 0.f;
#pragma unroll
        for (int i = 0; i < 8; i++) { float x; asm volatile("ld.shared.f32 %0, [%1];" : "=f"(x) : "r"(sb + OFF_RED + (i * 24 + tid) * 4)); s += x; }
        const uint32_t word = ((epoch + 1) << 16) | (pack_bf16(s, 0.f) & 0xffffu);
        asm volatile("st.relaxed.gpu.global.u32 [%0], %1;" :: "l"(g_mod + blockIdx.x * 24 + tid), "r"(word) : "memory");
      }
    }
    STAMP(1);
    uint32_t q[32];
    {
      uint32_t a[128];
      bar_sync(BAR_SOLO + cw, 160);
      {
        const uint32_t row = (tid >> 5) * 16 + (lane & 15);
        const uint32_t base = sb + row * 128, xr = row & 7, hi = lane >> 4;
#pragma unroll
        for (int kk = 0; kk < 32; kk++)
          ldsm4(base + (kk >> 2) * 16384 + (((((kk & 3) << 1) + hi) ^ xr) << 4), a[4*kk], a[4*kk+1], a[4*kk+2], a[4*kk+3]);
      }
      fence_regs(a);
      bar_sync(BAR_SOLO + cw, 160);
      float s0 = 0.f, q0 = 0.f, s1 = 0.f, q1 = 0.f;
#pragma unroll
      for (int kk = 0; kk < 32; kk++) {
        if (kk % 4 == 0) sched_fence();
        const float x0 = bf_lo(a[4*kk]), x1 = bf_hi(a[4*kk]), x2 = bf_lo(a[4*kk+2]), x3 = bf_hi(a[4*kk+2]);
        const float y0 = bf_lo(a[4*kk+1]), y1 = bf_hi(a[4*kk+1]), y2 = bf_lo(a[4*kk+3]), y3 = bf_hi(a[4*kk+3]);
        s0 += (x0 + x1) + (x2 + x3); q0 = fmaf(x0, x0, fmaf(x1, x1, fmaf(x2, x2, fmaf(x3, x3, q0))));
        s1 += (y0 + y1) + (y2 + y3); q1 = fmaf(y0, y0, fmaf(y1, y1, fmaf(y2, y2, fmaf(y3, y3, q1))));
        if ((kk >> 2) == hg) {
          __stcg(xacc + (2*kk) * 128, make_float4(x0, x1, y0, y1));
          __stcg(xacc + (2*kk+1) * 128, make_float4(x2, x3, y2, y3));
        }
      }
      fence_regs(a);
      bar_sync(BAR_WG + cw, 128);
      if ((tid & 127) == 0) flag_arrive(cnt + CNT_INIT * 1024);
      STAMP(2);
#pragma unroll
      for (int u = 0; u < 3; u++) {
        const int v0 = 4 * (tid + 256 * u);
        const uint4 wv = tagged_wait(g_mod + v0, (epoch + 1) & 0xffffu);
        const uint32_t x[4] = {wv.x, wv.y, wv.z, wv.w};
        const int part = v0 >> 9;
#pragma unroll
        for (int e = 0; e < 4; e++) {
          const int col = (v0 + e) & 511;
          float val = bf_lo(x[e]);
          if (part == 2 || part == 5) sts32(sb + (part == 2 ? OFF_GA : OFF_GB) + col * 4, val);
          else {
            const bool isc = (part == 1 || part == 4);
            if (isc) val = bf_round(1.f + val);
            sts32(sb + (part < 3 ? OFF_LN1 : OFF_LN2) + (col >> 4) * 128 + (isc ? 0 : 64) + ((col >> 1) & 3) * 16 + (((col >> 3) & 1) * 2 + (col & 1)) * 4, val);
          }
        }
      }
      bar_sync(BAR_CONS, 256);
      if (blockIdx.x == 0 && tid == 0) asm volatile("st.relaxed.gpu.global.u32 [%0], %1;" :: "l"(&g_epoch), "r"(epoch + 1) : "memory");
      STAMP(3);
      ln_apply(a, s0, q0, s1, q1, sb + OFF_LN1 + t4 * 16);
      STAMP(4);

      if (cw == 1) bar_arrive(BAR_PP, 288);
      float acc[64];
      auto qhead = [&]() {
#pragma unroll
        for (int kc = 0; kc < 4; kc++) {
          const uint32_t lo = nxt() | LBO_BOX;
          pp_enter();
          fence_regs(acc); fence_regs(a);
          wg_fence();
#pragma unroll
          for (int k = 0; k < 8; k++)
            wgmma_n128<1>(acc, a[32*kc+4*k], a[32*kc+4*k+1], a[32*kc+4*k+2], a[32*kc+4*k+3], desc_from(lo + k*128, HI_SW128), kc + k > 0);
          wg_commit();
          pp_leave();
          wg_wait<0>();
          fence_regs(acc);
        }
      };
#pragma unroll 1
      for (int h = 0; h < 3; h++) {
        qhead();
#pragma unroll
        for (int i = 0; i < 8; i++)
          __stcg(stash + (h*8 + i) * 256, make_uint4(pack_bf16(acc[8*i], acc[8*i+1]), pack_bf16(acc[8*i+2], acc[8*i+3]), pack_bf16(acc[8*i+4], acc[8*i+5]), pack_bf16(acc[8*i+6], acc[8*i+7])));
      }
      qhead();
#pragma unroll
      for (int i = 0; i < 32; i++) q[i] = pack_bf16(acc[2*i], acc[2*i+1]);
    }
    STAMP(5);

    uint32_t a[128];
    {
      const float C = 0.08838834764831845f * 1.4426950408889634f;
      const float BIG = 2.8147498e14f;
      float o[64], s[64]; uint32_t p[32];
      float mc0, mc1;
      float l[4] = {0.f, 0.f, 0.f, 0.f};
      auto issue_qk = [&](uint32_t lo) {
        lo |= 1u << 16;
#pragma unroll
        for (int k = 0; k < 8; k++)
          wgmma_n128<0>(s, q[4*k], q[4*k+1], q[4*k+2], q[4*k+3], desc_from(lo + (k/4)*1024 + (k%4)*2, HI_SW128), k > 0);
        wg_commit();
      };
      auto issue_pv = [&](uint32_t lo, int accum) {
        lo |= LBO_BOX;
#pragma unroll
        for (int k = 0; k < 8; k++)
          wgmma_n128<1>(o, p[4*k], p[4*k+1], p[4*k+2], p[4*k+3], desc_from(lo + k*128, HI_SW128), k > 0 ? 1 : accum);
        wg_commit();
      };
      auto row_max = [&](float& x0, float& x1) {
        x0 = fmaxf(s[0], s[1]); x1 = fmaxf(s[2], s[3]);
#pragma unroll
        for (int j = 1; j < 16; j++) { x0 = fmaxf(x0, fmaxf(s[4*j], s[4*j+1])); x1 = fmaxf(x1, fmaxf(s[4*j+2], s[4*j+3])); }
        x0 = fmaxf(x0, __shfl_xor_sync(0xffffffff, x0, 1)); x1 = fmaxf(x1, __shfl_xor_sync(0xffffffff, x1, 1));
        x0 = fmaxf(x0, __shfl_xor_sync(0xffffffff, x0, 2)); x1 = fmaxf(x1, __shfl_xor_sync(0xffffffff, x1, 2));
        x0 *= C; x1 *= C;
      };
      auto e_fma = [&](int e) { asm volatile("fma.rn.f32 %0, %0, %1, %2;" : "+f"(s[e]) : "f"(C), "f"((e & 2) ? -mc1 : -mc0)); };
      auto e_ex2 = [&](int e) { asm volatile("ex2.approx.ftz.f32 %0, %0;" : "+f"(s[e])); };
      auto e_add = [&](int e) { asm volatile("add.f32 %0, %0, %1;" : "+f"(l[e & 3]) : "f"(s[e])); };
      auto e_cvt = [&](int c) { asm volatile("cvt.rn.bf16x2.f32 %0, %1, %2;" : "=r"(p[c]) : "f"(s[2*c+1]), "f"(s[2*c])); };
      auto inv_sums = [&](float pl0, float pl1, float& i0, float& i1) {
        pl0 += __shfl_xor_sync(0xffffffff, pl0, 1); pl1 += __shfl_xor_sync(0xffffffff, pl1, 1);
        pl0 += __shfl_xor_sync(0xffffffff, pl0, 2); pl1 += __shfl_xor_sync(0xffffffff, pl1, 2);
        i0 = rcp(pl0); i1 = rcp(pl1);
      };
      auto refresh = [&](uint32_t klo, float pl0, float pl1) {
        float x0 = l[0] + l[1], x1 = l[2] + l[3];
        if (!__any_sync(0xffffffff, !(fmaxf(x0, x1) < BIG))) return;
        if (__all_sync(0xffffffff, x0 + x1 < 3.0e38f)) {
          x0 = fmaxf(x0, __shfl_xor_sync(0xffffffff, x0, 1)); x1 = fmaxf(x1, __shfl_xor_sync(0xffffffff, x1, 1));
          x0 = fmaxf(x0, __shfl_xor_sync(0xffffffff, x0, 2)); x1 = fmaxf(x1, __shfl_xor_sync(0xffffffff, x1, 2));
          const int e0 = min(max(((__float_as_int(x0) >> 23) & 0xff) - 127, 0), 126), e1 = min(max(((__float_as_int(x1) >> 23) & 0xff) - 127, 0), 126);
          const float f0 = __int_as_float((127 - e0) << 23), f1 = __int_as_float((127 - e1) << 23);
          mc0 += (float)e0; mc1 += (float)e1;
          l[0] *= f0; l[1] *= f0; l[2] *= f1; l[3] *= f1;
#pragma unroll
          for (int j = 0; j < 16; j++) {
            o[4*j] *= f0; o[4*j+1] *= f0; o[4*j+2] *= f1; o[4*j+3] *= f1;
            p[2*j] = pack_bf16(s[4*j] * f0, s[4*j+1] * f0); p[2*j+1] = pack_bf16(s[4*j+2] * f1, s[4*j+3] * f1);
          }
        } else {
          const uint32_t kb = (sb & ~0x3FFFFu) + (klo << 4) + (lane & 7) * 128;
#pragma unroll
          for (int j = 0; j < 16; j++) {
            sched_fence();
            s[4*j] = s[4*j+1] = s[4*j+2] = s[4*j+3] = 0.f;
#pragma unroll
            for (int k2 = 0; k2 < 4; k2++) {
              uint32_t b0, b1, b2, b3;
              ldsm4(kb + j * 1024 + (k2 >> 1) * 16384 + (((((k2 & 1) << 2) + (lane >> 3)) ^ (lane & 7)) << 4), b0, b1, b2, b3);
              asm volatile("mma.sync.aligned.m16n8k16.row.col.f32.bf16.bf16.f32 {%0,%1,%2,%3}, {%4,%5,%6,%7}, {%8,%9}, {%0,%1,%2,%3};"
                : "+f"(s[4*j]), "+f"(s[4*j+1]), "+f"(s[4*j+2]), "+f"(s[4*j+3]) : "r"(q[8*k2]), "r"(q[8*k2+1]), "r"(q[8*k2+2]), "r"(q[8*k2+3]), "r"(b0), "r"(b1));
              asm volatile("mma.sync.aligned.m16n8k16.row.col.f32.bf16.bf16.f32 {%0,%1,%2,%3}, {%4,%5,%6,%7}, {%8,%9}, {%0,%1,%2,%3};"
                : "+f"(s[4*j]), "+f"(s[4*j+1]), "+f"(s[4*j+2]), "+f"(s[4*j+3]) : "r"(q[8*k2+4]), "r"(q[8*k2+5]), "r"(q[8*k2+6]), "r"(q[8*k2+7]), "r"(b2), "r"(b3));
            }
          }
          row_max(x0, x1);
          x0 = fmaxf(x0, mc0); x1 = fmaxf(x1, mc1);
          const float f0 = ex2(mc0 - x0), f1 = ex2(mc1 - x1);
          mc0 = x0; mc1 = x1;
          l[0] = pl0 * f0; l[1] = 0.f; l[2] = pl1 * f1; l[3] = 0.f;
#pragma unroll
          for (int e = 0; e < 64; e++) {
            o[e] *= (e & 2) ? f1 : f0;
            s[e] = ex2(fmaf(s[e], C, (e & 2) ? -mc1 : -mc0));
            l[e & 3] += s[e];
          }
#pragma unroll
          for (int c = 0; c < 32; c++) p[c] = pack_bf16(s[2*c], s[2*c+1]);
        }
      };
      {
        const uint32_t klo = nxt();
        pp_enter();
        fence_regs(q); fence_regs(s);
        wg_fence();
        issue_qk(klo);
        pp_leave();
        wg_wait<0>();
        fence_regs(s);
        row_max(mc0, mc1);
        l[0] = l[1] = l[2] = l[3] = 0.f;
#pragma unroll
        for (int e = 0; e < 64; e++) { e_fma(e); e_ex2(e); e_add(e); if (e & 1) e_cvt(e >> 1); }
      }
#pragma unroll 1
      for (int it = 1; it < 64; it++) {
        const int j = it & 15;
        const uint32_t klo = nxt(), vlo = nxt();
        pp_enter();
        fence_regs(q); fence_regs(s); fence_regs(o); fence_regs(p);
        wg_fence();
        issue_qk(klo);
        issue_pv(vlo, j != 1);
        pp_leave();
        wg_wait<1>();
        fence_regs(s); fence_regs(q);
        float pl0 = l[0] + l[1], pl1 = l[2] + l[3];
        if (j == 0) { row_max(mc0, mc1); l[0] = l[1] = l[2] = l[3] = 0.f; }
        constexpr int LF = 2, LA = 4, SP = 32;
        e_fma(0); e_fma(1);
        int cvt_done = 0;
#pragma unroll
        for (int e = 0; e < 64; e++) {
          if (e % 2 == 0) sched_fence();
          if (e == SP) {
            wg_wait<0>();
            fence_regs(o); fence_regs(p);
            if (j == 0) {
              float i0, i1; inv_sums(pl0, pl1, i0, i1);
              uint4* op = stash + ((it >> 4) - 1) * 8 * 256;
#pragma unroll
              for (int i = 0; i < 8; i++)
                __stcg(op + i * 256, make_uint4(pack_bf16(o[8*i] * i0, o[8*i+1] * i0), pack_bf16(o[8*i+2] * i1, o[8*i+3] * i1),
                                                pack_bf16(o[8*i+4] * i0, o[8*i+5] * i0), pack_bf16(o[8*i+6] * i1, o[8*i+7] * i1)));
              pl0 = 0.f; pl1 = 0.f;
            }
          }
          e_ex2(e);
          if (e + LF < 64) e_fma(e + LF);
          if (e >= LA) e_add(e - LA);
          if (e >= SP) {
            int target = (e - SP + 1) * 32 / (64 - SP); const int lim = (e - LA + 1) / 2; if (target > lim) target = lim;
#pragma unroll
            for (int c = 0; c < 32; c++) if (c >= cvt_done && c < target) e_cvt(c);
            cvt_done = target > cvt_done ? target : cvt_done;
          }
        }
#pragma unroll
        for (int e = 64 - LA; e < 64; e++) e_add(e);
#pragma unroll
        for (int c = 0; c < 32; c++) if (c >= cvt_done) e_cvt(c);
        refresh(klo, pl0, pl1);
        if (j == 15 && it < 63) {
          const uint4* qp = stash + (it >> 4) * 8 * 256;
#pragma unroll
          for (int i = 0; i < 8; i++) { const uint4 v = __ldcg(qp + i * 256); q[4*i] = v.x; q[4*i+1] = v.y; q[4*i+2] = v.z; q[4*i+3] = v.w; }
        }
      }
      {
        const uint32_t vlo = nxt();
        pp_enter();
        fence_regs(o); fence_regs(p);
        wg_fence();
        issue_pv(vlo, 1);
        pp_leave();
#pragma unroll
        for (int i = 0; i < 24; i++) { const uint4 v = __ldcg(stash + i * 256); a[4*i] = v.x; a[4*i+1] = v.y; a[4*i+2] = v.z; a[4*i+3] = v.w; }
        float i0, i1; inv_sums(l[0] + l[1], l[2] + l[3], i0, i1);
        wg_wait<0>();
        fence_regs(o);
#pragma unroll
        for (int i = 0; i < 32; i++) a[96 + i] = pack_bf16(o[2*i] * ((i & 1) ? i1 : i0), o[2*i+1] * ((i & 1) ? i1 : i0));
      }
    }
    STAMP(6);
    const uint32_t target = (epoch + 1) * 8;
    auto red_chunk = [&](float (&d)[32], int cc, uint32_t gate) {
#pragma unroll
      for (int j = 0; j < 8; j++) {
        const float2 gv = lds64(gate + cc * 256 + j * 32);
        red128(xacc + (cc * 8 + j) * 128, d[4*j] * gv.x, d[4*j+1] * gv.y, d[4*j+2] * gv.x, d[4*j+3] * gv.y);
      }
    };
    {
      float d0[32], d1[32];
      const uint32_t gate = sb + OFF_GA + t4 * 8;
      flag_wait(cnt + CNT_INIT * 1024, target);
      auto ostep = [&](float (&d)[32], const int half) {
        const uint32_t lo = nxt() | LBO_BOX;
        pp_enter();
        fence_regs(d); fence_regs(a);
        wg_fence();
#pragma unroll
        for (int k = 0; k < 16; k++)
          wgmma_n64<1>(d, a[64*half+4*k], a[64*half+4*k+1], a[64*half+4*k+2], a[64*half+4*k+3], desc_from(lo + (k/8)*1024 + (k%8)*128, HI_SW128), half + k > 0);
        wg_commit();
        pp_leave();
      };
#pragma unroll 1
      for (int c = 0; c < 8; c += 2) {
        ostep(d0, 0);
        if (c > 0) red_chunk(d1, (c - 1 + hg) & 7, gate);
        sched_fence(); wg_wait<0>(); fence_regs(d0);
        ostep(d0, 1);
        wg_wait<0>(); fence_regs(d0);
        ostep(d1, 0);
        red_chunk(d0, (c + hg) & 7, gate);
        sched_fence(); wg_wait<0>(); fence_regs(d1);
        ostep(d1, 1);
        wg_wait<0>(); fence_regs(d1);
      }
      red_chunk(d1, (7 + hg) & 7, gate);
    }
    STAMP(7);
    bar_sync(BAR_WG + cw, 128);
    if ((tid & 127) == 0) { flag_arrive(cnt + CNT_O * 1024); flag_wait(cnt + CNT_O * 1024, target); }
    bar_sync(BAR_WG + cw, 128);
    STAMP(8);
    {
      float s0 = 0.f, q0 = 0.f, s1 = 0.f, q1 = 0.f;
#pragma unroll
      for (int j = 0; j < 64; j++) {
        const float4 v = __ldcg(xacc + j * 128);
        s0 += v.x + v.y; q0 = fmaf(v.x, v.x, fmaf(v.y, v.y, q0));
        s1 += v.z + v.w; q1 = fmaf(v.z, v.z, fmaf(v.w, v.w, q1));
        a[2*j] = pack_bf16(v.x, v.y); a[2*j+1] = pack_bf16(v.z, v.w);
      }
      fence_regs(a);
      bar_sync(BAR_WG + cw, 128);
      if ((tid & 127) == 0) flag_arrive(cnt + CNT_READ * 1024);
      STAMP(9);
      ln_apply(a, s0, q0, s1, q1, sb + OFF_LN2 + t4 * 16);
    }
    STAMP(10);
    uint32_t act[56];
    {
      float d0[32], d1[32];
      auto gstep = [&](float (&d)[32], const int half) {
        const uint32_t lo = nxt() | LBO_BOX;
        pp_enter();
        fence_regs(d); fence_regs(a);
        wg_fence();
#pragma unroll
        for (int k = 0; k < 16; k++)
          wgmma_n64<1>(d, a[64*half+4*k], a[64*half+4*k+1], a[64*half+4*k+2], a[64*half+4*k+3], desc_from(lo + k*64, HI_SW64), half + k > 0);
        wg_commit();
        pp_leave();
      };
      auto swiglu = [&](float (&d)[32], uint32_t (&r)[8]) {
#pragma unroll
        for (int i = 0; i < 8; i++) r[i] = pack_bf16(silu_f(d[2*i]) * d[16+2*i], silu_f(d[2*i+1]) * d[16+2*i+1]);
      };
      auto swiglu_stash = [&](float (&d)[32], int pass) {
        uint32_t r[8]; swiglu(d, r);
        __stcg(stash + (2*pass) * 256, make_uint4(r[0], r[1], r[2], r[3]));
        __stcg(stash + (2*pass+1) * 256, make_uint4(r[4], r[5], r[6], r[7]));
      };
#pragma unroll 1
      for (int ps = 0; ps < 6; ps += 2) {
        gstep(d0, 0);
        if (ps > 0) swiglu_stash(d1, ps - 1);
        sched_fence(); wg_wait<0>(); fence_regs(d0);
        gstep(d0, 1);
        wg_wait<0>(); fence_regs(d0);
        gstep(d1, 0);
        swiglu_stash(d0, ps);
        sched_fence(); wg_wait<0>(); fence_regs(d1);
        gstep(d1, 1);
        wg_wait<0>(); fence_regs(d1);
      }
      gstep(d0, 0);
      uint32_t r5[8], r6[8];
      swiglu(d1, r5);
      fence_regs(r5); sched_fence(); wg_wait<0>(); fence_regs(d0);
      gstep(d0, 1);
      wg_wait<0>(); fence_regs(d0);
#pragma unroll
      for (int i = 0; i < 10; i++) { const uint4 v = __ldcg(stash + i * 256); act[4*i] = v.x; act[4*i+1] = v.y; act[4*i+2] = v.z; act[4*i+3] = v.w; }
      swiglu(d0, r6);
#pragma unroll
      for (int i = 0; i < 8; i++) { act[40 + i] = r5[i]; act[48 + i] = r6[i]; }
    }
    STAMP(11);
    {
      float d0[32], d1[32];
      const uint32_t gate = sb + OFF_GB + t4 * 8;
      flag_wait(cnt + CNT_READ * 1024, target);
      auto dstep = [&](float (&d)[32], bool leave) {
        const uint32_t lo = nxt() | LBO_BOX;
        pp_enter();
        fence_regs(d); fence_regs(act);
        wg_fence();
#pragma unroll
        for (int k = 0; k < 14; k++)
          wgmma_n64<1>(d, act[4*k], act[4*k+1], act[4*k+2], act[4*k+3], desc_from(lo + (k/7)*1024 + (k%7)*128, HI_SW128), k > 0);
        wg_commit();
        if (leave) pp_leave();
      };
#pragma unroll 1
      for (int c = 0; c < 8; c += 2) {
        dstep(d0, true);
        if (c > 0) red_chunk(d1, (c - 1 + hg) & 7, gate);
        sched_fence(); wg_wait<0>(); fence_regs(d0);
        dstep(d1, c < 6 || cw == 0);
        red_chunk(d0, (c + hg) & 7, gate);
        sched_fence(); wg_wait<0>(); fence_regs(d1);
      }
      red_chunk(d1, (7 + hg) & 7, gate);
    }
    STAMP(12);
    bar_sync(BAR_WG + cw, 128);
    if ((tid & 127) == 0) { flag_arrive(cnt + CNT_D * 1024); flag_wait(cnt + CNT_D * 1024, target); }
    bar_sync(BAR_WG + cw, 128);
    STAMP(13);
    {
      float4 v[8];
#pragma unroll
      for (int j = 0; j < 8; j++) v[j] = __ldcg(xacc + (hg * 8 + j) * 128);
      uint32_t* op = out + (size_t)(rb * 128 + (tid >> 5) * 16 + (lane >> 2)) * 256 + hg * 32 + t4;
#pragma unroll
      for (int j = 0; j < 8; j++) { op[j * 4] = pack_bf16(v[j].x, v[j].y); op[8 * 256 + j * 4] = pack_bf16(v[j].z, v[j].w); }
    }
    STAMP(14);
    cluster_sync();
  }
}

typedef CUresult (*EncodeFn)(CUtensorMap*, CUtensorMapDataType, cuuint32_t, void*, const cuuint64_t*, const cuuint64_t*, const cuuint32_t*,
                             const cuuint32_t*, CUtensorMapInterleave, CUtensorMapSwizzle, CUtensorMapL2promotion, CUtensorMapFloatOOBfill);

void make_map(EncodeFn enc, CUtensorMap* m, const void* ptr, uint64_t rows, uint64_t cols, uint32_t box_rows, uint32_t box_cols, CUtensorMapSwizzle sw) {
  cuuint64_t dims[2] = {cols, rows};
  cuuint64_t strides[1] = {cols * 2};
  cuuint32_t box[2] = {box_cols, box_rows};
  cuuint32_t es[2] = {1, 1};
  enc(m, CU_TENSOR_MAP_DATA_TYPE_BFLOAT16, 2, const_cast<void*>(ptr), dims, strides, box, es, CU_TENSOR_MAP_INTERLEAVE_NONE, sw,
      CU_TENSOR_MAP_L2_PROMOTION_L2_128B, CU_TENSOR_MAP_FLOAT_OOB_FILL_NONE);
}

}

extern "C" void kernel_launch(void* const* d_in, const int* in_sizes, int n_in, void* d_out, int out_size) {
  (void)in_sizes; (void)n_in; (void)out_size;
  static EncodeFn enc = nullptr;
  if (!enc) {
    void* fn = nullptr; cudaDriverEntryPointQueryResult qr;
    cudaGetDriverEntryPoint("cuTensorMapEncodeTiled", &fn, cudaEnableDefault, &qr);
    enc = (EncodeFn)fn;
    cudaFuncSetAttribute(block_kernel, cudaFuncAttributeMaxDynamicSharedMemorySize, SMEM_BYTES);
  }
  Maps maps;
  const CUtensorMapSwizzle S128 = CU_TENSOR_MAP_SWIZZLE_128B, S64 = CU_TENSOR_MAP_SWIZZLE_64B;
  make_map(enc, &maps.x, d_in[0], 2048, 512, 128, 64, S128);
  make_map(enc, &maps.k, d_in[1], 16384, 128, 128, 64, S128);
  make_map(enc, &maps.v, d_in[2], 16384, 128, 128, 64, S128);
  make_map(enc, &maps.wq, d_in[3], 512, 4096, 128, 64, S128);
  make_map(enc, &maps.wo, d_in[4], 4096, 512, 128, 64, S128);
  make_map(enc, &maps.wg, d_in[6], 512, 1792, 256, 32, S64);
  make_map(enc, &maps.wu, d_in[7], 512, 1792, 256, 32, S64);
  make_map(enc, &maps.wd, d_in[8], 1792, 512, 112, 64, S128);
  cudaLaunchConfig_t cfg = {};
  cfg.gridDim = dim3(128); cfg.blockDim = dim3(384); cfg.dynamicSmemBytes = SMEM_BYTES; cfg.stream = cudaStreamPerThread;
  cudaLaunchAttribute at[1];
  at[0].id = cudaLaunchAttributeClusterDimension; at[0].val.clusterDim.x = 2; at[0].val.clusterDim.y = 1; at[0].val.clusterDim.z = 1;
  cfg.attrs = at; cfg.numAttrs = 1;
  cudaLaunchKernelEx(&cfg, block_kernel, maps, (const __nv_bfloat16*)d_in[9], (const uint4*)d_in[10], (uint32_t*)d_out);
}
```

```cpp
#include <cuda_runtime.h>
#include <cuda_bf16.h>
#include <cuda.h>
#include <stdint.h>
#include <stddef.h>

namespace {

constexpr int NS = 5;
constexpr int SLOT = 32768;
constexpr int OFF_DSM = NS * SLOT;
constexpr int OFF_RES = OFF_DSM + 32768;
constexpr int OFF_BAR = OFF_RES + 16384;
constexpr int OFF_LN1 = OFF_BAR + 256;
constexpr int OFF_LN2 = OFF_LN1 + 2048;
constexpr int OFF_GA = OFF_LN2 + 2048;
constexpr int OFF_GB = OFF_GA + 2048;
constexpr int OFF_SC = OFF_GB + 2048;
constexpr int OFF_RED = OFF_SC + 2048;
constexpr int OFF_EPOCH = OFF_RED + 2048;
constexpr int SMEM_BYTES = OFF_EPOCH + 128;

constexpr int BAR_PP = 1;
constexpr int BAR_SOLO = 3;
constexpr int BAR_CONS = 7;
constexpr int BAR_AUX = 8;
constexpr int BAR_AUX2 = 9;

constexpr float QSCALE = 0.08838834764831845f * 1.4426950408889634f;
constexpr int DELTA = 100;
constexpr int STASH = 48;
constexpr int MAX_POLL = 1 << 20;
enum { CNT_X = 0, CNT_O = 1, CNT_D = 2, CNT_KINDS = 3 };

struct Scratch {
  uint32_t epoch, pad[31];
  uint32_t part[8 * 1024];
  uint32_t mod[2048];
  uint32_t cnt[CNT_KINDS * 128 * 8 * 8];
  uint4 x1[32 * 40 * 128];
  uint4 stash[128 * STASH * 256];
  uint4 mbox[32 * 8 * 3 * 4 * 128];
};
__device__ Scratch g_scratch;

template<int TRANSB> __device__ __forceinline__ void wgmma_n128(float (&d)[64], uint32_t a0, uint32_t a1, uint32_t a2, uint32_t a3, uint64_t descB, int scaleD) {
  asm volatile("{\n.reg .pred p;\n"
    "setp.ne.b32 p, %69, 0;\n"
    "wgmma.mma_async.sync.aligned.m64n128k16.f32.bf16.bf16 "
    "{%0, %1, %2, %3, %4, %5, %6, %7, %8, %9, %10, %11, %12, %13, %14, %15, "
    "%16, %17, %18, %19, %20, %21, %22, %23, %24, %25, %26, %27, %28, %29, %30, %31, "
    "%32, %33, %34, %35, %36, %37, %38, %39, %40, %41, %42, %43, %44, %45, %46, %47, "
    "%48, %49, %50, %51, %52, %53, %54, %55, %56, %57, %58, %59, %60, %61, %62, %63}, "
    "{%64, %65, %66, %67}, %68, p, 1, 1, %70;\n}\n"
    : "+f"(d[0]), "+f"(d[1]), "+f"(d[2]), "+f"(d[3]), "+f"(d[4]), "+f"(d[5]), "+f"(d[6]), "+f"(d[7]),
      "+f"(d[8]), "+f"(d[9]), "+f"(d[10]), "+f"(d[11]), "+f"(d[12]), "+f"(d[13]), "+f"(d[14]), "+f"(d[15]),
      "+f"(d[16]), "+f"(d[17]), "+f"(d[18]), "+f"(d[19]), "+f"(d[20]), "+f"(d[21]), "+f"(d[22]), "+f"(d[23]),
      "+f"(d[24]), "+f"(d[25]), "+f"(d[26]), "+f"(d[27]), "+f"(d[28]), "+f"(d[29]), "+f"(d[30]), "+f"(d[31]),
      "+f"(d[32]), "+f"(d[33]), "+f"(d[34]), "+f"(d[35]), "+f"(d[36]), "+f"(d[37]), "+f"(d[38]), "+f"(d[39]),
      "+f"(d[40]), "+f"(d[41]), "+f"(d[42]), "+f"(d[43]), "+f"(d[44]), "+f"(d[45]), "+f"(d[46]), "+f"(d[47]),
      "+f"(d[48]), "+f"(d[49]), "+f"(d[50]), "+f"(d[51]), "+f"(d[52]), "+f"(d[53]), "+f"(d[54]), "+f"(d[55]),
      "+f"(d[56]), "+f"(d[57]), "+f"(d[58]), "+f"(d[59]), "+f"(d[60]), "+f"(d[61]), "+f"(d[62]), "+f"(d[63])
    : "r"(a0), "r"(a1), "r"(a2), "r"(a3), "l"(descB), "r"(scaleD), "n"(TRANSB));
}
template<int TRANSB> __device__ __forceinline__ void wgmma_n64(float (&d)[32], uint32_t a0, uint32_t a1, uint32_t a2, uint32_t a3, uint64_t descB, int scaleD) {
  asm volatile("{\n.reg .pred p;\n"
    "setp.ne.b32 p, %37, 0;\n"
    "wgmma.mma_async.sync.aligned.m64n64k16.f32.bf16.bf16 "
    "{%0, %1, %2, %3, %4, %5, %6, %7, %8, %9, %10, %11, %12, %13, %14, %15, "
    "%16, %17, %18, %19, %20, %21, %22, %23, %24, %25, %26, %27, %28, %29, %30, %31}, "
    "{%32, %33, %34, %35}, %36, p, 1, 1, %38;\n}\n"
    : "+f"(d[0]), "+f"(d[1]), "+f"(d[2]), "+f"(d[3]), "+f"(d[4]), "+f"(d[5]), "+f"(d[6]), "+f"(d[7]),
      "+f"(d[8]), "+f"(d[9]), "+f"(d[10]), "+f"(d[11]), "+f"(d[12]), "+f"(d[13]), "+f"(d[14]), "+f"(d[15]),
      "+f"(d[16]), "+f"(d[17]), "+f"(d[18]), "+f"(d[19]), "+f"(d[20]), "+f"(d[21]), "+f"(d[22]), "+f"(d[23]),
      "+f"(d[24]), "+f"(d[25]), "+f"(d[26]), "+f"(d[27]), "+f"(d[28]), "+f"(d[29]), "+f"(d[30]), "+f"(d[31])
    : "r"(a0), "r"(a1), "r"(a2), "r"(a3), "l"(descB), "r"(scaleD), "n"(TRANSB));
}

__device__ __forceinline__ uint32_t smem_u32(const void* p) { return (uint32_t)__cvta_generic_to_shared(p); }
__device__ __forceinline__ void wg_fence() { asm volatile("wgmma.fence.sync.aligned;" ::: "memory"); }
__device__ __forceinline__ void wg_commit() { asm volatile("wgmma.commit_group.sync.aligned;" ::: "memory"); }
template<int N> __device__ __forceinline__ void wg_wait() { asm volatile("wgmma.wait_group.sync.aligned %0;" :: "n"(N) : "memory"); }
template<int N> __device__ __forceinline__ void fence_regs(float (&d)[N]) {
#pragma unroll
  for (int i = 0; i < N; i++) asm volatile("" : "+f"(d[i]) :: "memory");
}
template<int N> __device__ __forceinline__ void fence_regs(uint32_t (&d)[N]) {
#pragma unroll
  for (int i = 0; i < N; i++) asm volatile("" : "+r"(d[i]) :: "memory");
}
__device__ __forceinline__ void sched_fence() { asm volatile("pmevent 0;" ::: "memory"); }
__device__ __forceinline__ void mbar_init(uint32_t bar, uint32_t cnt) { asm volatile("mbarrier.init.shared::cta.b64 [%0], %1;" :: "r"(bar), "r"(cnt) : "memory"); }
__device__ __forceinline__ void mbar_expect_tx(uint32_t bar, uint32_t bytes) { asm volatile("mbarrier.arrive.expect_tx.shared::cta.b64 _, [%0], %1;" :: "r"(bar), "r"(bytes) : "memory"); }
__device__ __forceinline__ bool mbar_test(uint32_t bar, uint32_t parity) {
  uint32_t ok;
  asm volatile("{\n.reg .pred p;\nmbarrier.test_wait.parity.shared::cta.b64 p, [%1], %2;\nselp.u32 %0, 1, 0, p;\n}" : "=r"(ok) : "r"(bar), "r"(parity) : "memory");
  return ok;
}
__device__ __forceinline__ void mbar_wait_warp(uint32_t bar, uint32_t parity, bool ready) {
  if (__all_sync(0xffffffff, ready)) return;
#pragma unroll 1
  for (int it = 0; it < 4000000; it++) if (__all_sync(0xffffffff, mbar_test(bar, parity))) break;
}
__device__ __forceinline__ void mbar_wait(uint32_t bar, uint32_t parity) {
  asm volatile("{\n.reg .pred p;\n.reg .u32 it;\nmov.u32 it, 0;\n"
    "LAB_WAIT:\n"
    "mbarrier.try_wait.parity.shared::cta.b64 p, [%0], %1;\n"
    "@p bra LAB_DONE;\n"
    "add.u32 it, it, 1;\n"
    "setp.lt.u32 p, it, 4000000;\n"
    "@p bra LAB_WAIT;\n"
    "trap;\n"
    "LAB_DONE:\n}" :: "r"(bar), "r"(parity) : "memory");
}
__device__ __forceinline__ void mbar_wait_sleep(uint32_t bar, uint32_t parity) {
  asm volatile("{\n.reg .pred p;\n.reg .u32 it;\nmov.u32 it, 0;\n"
    "LAB_WAIT:\n"
    "mbarrier.try_wait.parity.shared::cta.b64 p, [%0], %1, 100000;\n"
    "@p bra LAB_DONE;\n"
    "add.u32 it, it, 1;\n"
    "setp.lt.u32 p, it, 20000;\n"
    "@p bra LAB_WAIT;\n"
    "trap;\n"
    "LAB_DONE:\n}" :: "r"(bar), "r"(parity) : "memory");
}
__device__ __forceinline__ uint4 ld128(const uint4* p) {
  uint4 v;
  asm volatile("{\n.reg .b128 t;\n.reg .b64 a, b;\nld.relaxed.gpu.global.b128 t, [%4];\nmov.b128 {a, b}, t;\nmov.b64 {%0, %1}, a;\nmov.b64 {%2, %3}, b;\n}"
    : "=r"(v.x), "=r"(v.y), "=r"(v.z), "=r"(v.w) : "l"(p) : "memory");
  return v;
}
__device__ __forceinline__ void st128(uint4* p, uint32_t x, uint32_t y, uint32_t z, uint32_t w) {
  asm volatile("{\n.reg .b128 t;\n.reg .b64 a, b;\nmov.b64 a, {%1, %2};\nmov.b64 b, {%3, %4};\nmov.b128 t, {a, b};\nst.relaxed.gpu.global.b128 [%0], t;\n}"
    :: "l"(p), "r"(x), "r"(y), "r"(z), "r"(w) : "memory");
}
__device__ __forceinline__ uint4 tagged_wait(const uint32_t* p, uint32_t tag) {
  uint4 v;
  asm volatile("{\n.reg .pred p;\n.reg .u32 it, a, b;\nmov.u32 it, 0;\n"
    "LAB_WAIT:\n"
    "ld.relaxed.gpu.global.v4.u32 {%0, %1, %2, %3}, [%4];\n"
    "xor.b32 a, %0, %5;\n xor.b32 b, %1, %5;\n or.b32 a, a, b;\n xor.b32 b, %2, %5;\n or.b32 a, a, b;\n xor.b32 b, %3, %5;\n or.b32 a, a, b;\n"
    "setp.lt.u32 p, a, 65536;\n"
    "@p bra LAB_DONE;\n"
    "nanosleep.u32 500;\n"
    "add.u32 it, it, 1;\n"
    "setp.lt.u32 p, it, 4000000;\n"
    "@p bra LAB_WAIT;\n"
    "trap;\n"
    "LAB_DONE:\n}" : "=&r"(v.x), "=&r"(v.y), "=&r"(v.z), "=&r"(v.w) : "l"(p), "r"(tag << 16) : "memory");
  return v;
}
__device__ __forceinline__ void tma_load(uint32_t dst, const CUtensorMap* m, uint32_t bar, int c0, int c1) {
  asm volatile("cp.async.bulk.tensor.2d.shared::cluster.global.mbarrier::complete_tx::bytes [%0], [%1, {%3, %4}], [%2];"
    :: "r"(dst), "l"(m), "r"(bar), "r"(c0), "r"(c1) : "memory");
}
__device__ __forceinline__ void tma_load_mc(uint32_t dst, const CUtensorMap* m, uint32_t bar, int c0, int c1) {
  asm volatile("cp.async.bulk.tensor.2d.shared::cluster.global.mbarrier::complete_tx::bytes.multicast::cluster [%0], [%1, {%3, %4}], [%2], %5;"
    :: "r"(dst), "l"(m), "r"(bar), "r"(c0), "r"(c1), "h"((uint16_t)3) : "memory");
}
__device__ __forceinline__ void bar_sync(int id, int n) { asm volatile("bar.sync %0, %1;" :: "r"(id), "r"(n) : "memory"); }
__device__ __forceinline__ void bar_arrive(int id, int n) { asm volatile("bar.arrive %0, %1;" :: "r"(id), "r"(n) : "memory"); }
__device__ __forceinline__ float ex2(float x) { float y; asm("ex2.approx.ftz.f32 %0, %1;" : "=f"(y) : "f"(x)); return y; }
__device__ __forceinline__ float rcp(float x) { float y; asm("rcp.approx.ftz.f32 %0, %1;" : "=f"(y) : "f"(x)); return y; }
__device__ __forceinline__ uint32_t pack_bf16(float lo, float hi) { uint32_t r; asm("cvt.rn.bf16x2.f32 %0, %1, %2;" : "=r"(r) : "f"(hi), "f"(lo)); return r; }
__device__ __forceinline__ float bf_lo(uint32_t v) { return __uint_as_float(v << 16); }
__device__ __forceinline__ float bf_hi(uint32_t v) { return __uint_as_float(v & 0xffff0000u); }
__device__ __forceinline__ float bf_round(float x) { return bf_lo(pack_bf16(x, 0.f)); }
__device__ __forceinline__ uint64_t desc_from(uint32_t lo, uint32_t hi) { uint64_t d; asm("mov.b64 %0, {%1, %2};" : "=l"(d) : "r"(lo), "r"(hi)); return d; }
__device__ __forceinline__ float2 lds64(uint32_t a) { float2 v; asm volatile("ld.shared.v2.f32 {%0,%1}, [%2];" : "=f"(v.x), "=f"(v.y) : "r"(a)); return v; }
__device__ __forceinline__ uint32_t lds32(uint32_t a) { uint32_t v; asm volatile("ld.shared.u32 %0, [%1];" : "=r"(v) : "r"(a) : "memory"); return v; }
__device__ __forceinline__ void sts32(uint32_t a, float v) { asm volatile("st.shared.f32 [%0], %1;" :: "r"(a), "f"(v) : "memory"); }
__device__ __forceinline__ void ldsm4(uint32_t a, uint32_t& r0, uint32_t& r1, uint32_t& r2, uint32_t& r3) {
  asm volatile("ldmatrix.sync.aligned.m8n8.x4.shared.b16 {%0,%1,%2,%3}, [%4];" : "=r"(r0), "=r"(r1), "=r"(r2), "=r"(r3) : "r"(a) : "memory");
}
__device__ __forceinline__ float silu_f(float v) { return v * rcp(1.f + ex2(v * -1.4426950408889634f)); }

constexpr uint32_t HI_SW128 = (1024 >> 4) | (1u << 30);
constexpr uint32_t HI_SW64 = (512 >> 4) | (2u << 30);
constexpr uint32_t LBO_BOX = (16384u >> 4) << 16;

struct Maps { CUtensorMap x, wq, k, v, wo, wg, wu, wd; };

__device__ __forceinline__ void hmma(float (&c)[4], uint32_t a0, uint32_t a1, uint32_t a2, uint32_t a3, uint32_t b0, uint32_t b1) {
  asm volatile("mma.sync.aligned.m16n8k16.row.col.f32.bf16.bf16.f32 {%0,%1,%2,%3}, {%4,%5,%6,%7}, {%8,%9}, {%0,%1,%2,%3};"
    : "+f"(c[0]), "+f"(c[1]), "+f"(c[2]), "+f"(c[3]) : "r"(a0), "r"(a1), "r"(a2), "r"(a3), "r"(b0), "r"(b1));
}
__device__ __forceinline__ void hmma8(float (&c)[4], uint32_t a0, uint32_t a1, uint32_t b0) {
  asm volatile("mma.sync.aligned.m16n8k8.row.col.f32.bf16.bf16.f32 {%0,%1,%2,%3}, {%4,%5}, {%6}, {%0,%1,%2,%3};"
    : "+f"(c[0]), "+f"(c[1]), "+f"(c[2]), "+f"(c[3]) : "r"(a0), "r"(a1), "r"(b0));
}
__device__ __forceinline__ uint32_t hfma2(uint32_t a, uint32_t b, uint32_t c) { uint32_t d; asm("fma.rn.bf16x2 %0, %1, %2, %3;" : "=r"(d) : "r"(a), "r"(b), "r"(c)); return d; }

__device__ __forceinline__ void ln_coef(float s, float q, uint32_t& r2, uint32_t& b2) {
  const float m = s * (1.f / 512);
  const float r = bf_round(rsqrtf(fmaxf(q * (1.f / 512) - m * m, 0.f) + 1e-5f));
  r2 = pack_bf16(r, r); b2 = pack_bf16(-m * r, -m * r);
}
__device__ __forceinline__ void ln_apply(uint32_t (&a)[128], const uint32_t (&rb)[4], uint32_t prm, const int k0, const int k1) {
#pragma unroll
  for (int kk = k0; kk < k1; kk++) {
    if (kk == 0) sched_fence();
    uint32_t c0, c1, s0, s1;
    asm volatile("ld.shared.v4.u32 {%0,%1,%2,%3}, [%4];" : "=r"(c0), "=r"(c1), "=r"(s0), "=r"(s1) : "r"(prm + kk * 64));
    a[4*kk]   = hfma2(hfma2(a[4*kk],   rb[0], rb[1]), c0, s0);
    a[4*kk+1] = hfma2(hfma2(a[4*kk+1], rb[2], rb[3]), c0, s0);
    a[4*kk+2] = hfma2(hfma2(a[4*kk+2], rb[0], rb[1]), c1, s1);
    a[4*kk+3] = hfma2(hfma2(a[4*kk+3], rb[2], rb[3]), c1, s1);
  }
}

__device__ __forceinline__ void stage_mod(uint32_t sb, int part, int col, float v0, float v1, float v2, float v3) {
  if (part == 2 || part == 5) {
    asm volatile("st.shared.v4.f32 [%0], {%1,%2,%3,%4};" :: "r"(sb + (part == 2 ? OFF_GA : OFF_GB) + col * 4), "f"(v0), "f"(v1), "f"(v2), "f"(v3) : "memory");
  } else {
    const bool isc = (part == 1 || part == 4);
    if (isc) { v0 += 1.f; v1 += 1.f; v2 += 1.f; v3 += 1.f; }
    const uint32_t ad = sb + (part < 3 ? OFF_LN1 : OFF_LN2) + (col >> 4) * 64 + ((col >> 1) & 3) * 16 + (isc ? 0 : 8) + ((col >> 3) & 1) * 4;
    sts32(ad, __uint_as_float(pack_bf16(v0, v1))); sts32(ad + 16, __uint_as_float(pack_bf16(v2, v3)));
  }
}
__device__ __forceinline__ void publish_mod(uint32_t* dst, uint32_t epoch, float v) {
  asm volatile("st.relaxed.gpu.global.u32 [%0], %1;" :: "l"(dst), "r"(((epoch + 1) << 16) | (pack_bf16(v, 0.f) & 0xffffu)) : "memory");
}

__global__ void __cluster_dims__(2, 1, 1) __launch_bounds__(384, 1)
block_kernel(const __nv_bfloat16* __restrict__ cvec, const uint4* __restrict__ wmod, Scratch* __restrict__ scr,
             uint32_t* __restrict__ out, const __grid_constant__ Maps maps) {
  extern __shared__ __align__(1024) uint8_t smem_raw[];
  const uint32_t sb = smem_u32(smem_raw);
  const uint32_t bfull = sb + OFF_BAR, bempty = bfull + 64;
  const uint32_t rank = blockIdx.x & 1;
  const int wg = __shfl_sync(0xffffffff, threadIdx.x / 128, 0);
  const int gam = blockIdx.x >> 5;
  const int hg = gam * 2 + rank;
  const int rb = ((blockIdx.x >> 1) & 7) * 2 + ((blockIdx.x >> 4) & 1);
  auto chunk_at = [&](int c) { return ((gam + 1 + (c >> 1)) & 3) * 2 + ((c & 1) ? rank : rank ^ 1); };
  uint4 wm0 = {}, wm1 = {}; uint32_t epoch0 = 0; __nv_bfloat16 cv0 = {}, cv1 = {};
  if (wg != 0) {
    const uint32_t tid = threadIdx.x - 128, row = (blockIdx.x >> 4) * 64 + (tid >> 3), col = (blockIdx.x & 15) * 8 + (tid & 7);
    wm0 = __ldg(wmod + (row * 384 + col)); wm1 = __ldg(wmod + ((row + 32) * 384 + col));
    cv0 = cvec[row]; cv1 = cvec[row + 32];
    if (tid == 0) asm volatile("ld.relaxed.gpu.global.u32 %0, [%1];" : "=r"(epoch0) : "l"(&scr->epoch) : "memory");
  }
  if (wg == 0) {
    if (threadIdx.x == 0) {
      for (int i = 0; i < NS; i++) { mbar_init(bfull + i*8, 1); mbar_init(bempty + i*8, 4); }
      for (int i = 0; i < 16; i++) mbar_init(bfull + 128 + i*8, 1);
      asm volatile("fence.mbarrier_init.release.cluster;" ::: "memory");
    }
    if (threadIdx.x == 32) { asm volatile("prefetch.tensormap [%0];" :: "l"(&maps.x) : "memory"); asm volatile("prefetch.tensormap [%0];" :: "l"(&maps.wq) : "memory"); }
    __syncwarp();
    bar_arrive(0, 384);
    asm volatile("barrier.cluster.arrive.relaxed.aligned;" ::: "memory");
    asm volatile("setmaxnreg.dec.sync.aligned.u32 24;");
    if (threadIdx.x == 0) {
#pragma unroll 1
      for (int t = 0; t < 8; t++) {
        if (!(t & 1)) mbar_expect_tx(bfull + (t >> 1)*8, SLOT);
        tma_load(sb + t*16384, &maps.x, bfull + (t >> 1)*8, t*64, rb*128);
      }
    }
    __syncwarp();
    asm volatile("barrier.cluster.wait.aligned;" ::: "memory");
    const int warp = __shfl_sync(0xffffffff, threadIdx.x / 32, 0);
    const int lane = threadIdx.x & 31;
    if (warp == 0) {
      if (lane == 0) {
        uint32_t slot = 4, phase = 1;
        auto acquire = [&](uint32_t bytes) { mbar_wait_sleep(bempty + slot*8, phase); mbar_expect_tx(bfull + slot*8, bytes); };
        auto advance = [&]() { if (++slot == NS) { slot = 0; phase ^= 1; } };
        auto load2 = [&](const CUtensorMap* m0, const CUtensorMap* m1, int c0, int r0, int r1, uint32_t bytes) {
          acquire(bytes);
          tma_load(sb + slot*SLOT, m0, bfull + slot*8, c0, r0);
          tma_load(sb + slot*SLOT + 16384, m1, bfull + slot*8, c0, r1);
          advance();
        };
        mbar_wait(bfull + 24, 0);
#pragma unroll 1
        for (int t = 0; t < 16; t++) load2(&maps.wq, &maps.wq, gam*1024 + (t >> 3)*512 + rank*256 + ((t >> 1) & 3)*64, (t & 1)*256, (t & 1)*256 + 128, SLOT);
#pragma unroll 1
        for (int t = 0; t < 128; t++) {
          const bool isv = t > 1 && (!(t & 1) || t == 127);
          const int blk = isv ? (t >> 1) - 1 + (t == 127) : (t + 1) >> 1;
          acquire(SLOT);
          tma_load_mc(sb + slot*SLOT + rank*16384, isv ? &maps.v : &maps.k, bfull + slot*8, rank*64, (gam*2 + (blk >> 5))*2048 + (blk & 15)*128);
          advance();
        }
#pragma unroll 1
        for (int t = 0; t < 16; t++) { const int r0 = gam*1024 + (t & 1)*512 + rank*256; load2(&maps.wo, &maps.wo, chunk_at(t >> 1)*64, r0, r0 + 128, SLOT); }
#pragma unroll 1
        for (int t = 0; t < 14; t++) load2(&maps.wg, &maps.wu, hg*224 + (t >> 1)*32, (t & 1)*256, (t & 1)*256, SLOT);
#pragma unroll 1
        for (int t = 0; t < 8; t++) load2(&maps.wd, &maps.wd, chunk_at(t)*64, hg*224, hg*224 + 112, 28672);
      }
    } else if (warp <= 2) {
      const int cw = warp - 1;
      uint32_t rbar; asm("mapa.shared::cluster.u32 %0, %1, %2;" : "=r"(rbar) : "r"(bempty), "r"(lane & 1));
      uint32_t slot = 4, phase = 0, rel = 0;
      auto wait_full = [&]() { mbar_wait(bfull + slot*8, phase); if (++slot == NS) { slot = 0; phase ^= 1; } };
      auto release = [&]() {
        if (lane < 2) asm volatile("mbarrier.arrive.shared::cluster.b64 _, [%0];" :: "r"(rbar + rel*8) : "memory");
        if (++rel == NS) rel = 0;
      };
      bar_sync(BAR_SOLO + cw, 160);
#pragma unroll 1
      for (int t = 0; t < 4; t++) release();
      int prev = 0;
#pragma unroll 1
      for (int st = 0; st < 16 + 65 + 38; st++) {
        const int n = (st > 16 && st < 16 + 64) ? 2 : 1;
        wait_full(); if (n == 2) wait_full();
        bar_sync(BAR_PP + cw, 288);
        if (st <= 16 + 65 + 38 - NS) { if (prev >= 1) release(); if (prev == 2) release(); }
        prev = n;
      }
    } else {
      bar_sync(BAR_AUX, 160);
#pragma unroll 1
      for (int r = lane; r < 512; r += 32) sts32(sb + OFF_SC + r * 4, bf_round(silu_f(__bfloat162float(cvec[r]))));
      __syncwarp();
      float v[8] = {};
#pragma unroll 1
      for (uint32_t r = lane >> 1; r < 512; r += 16) {
        const uint4 w = __ldg(wmod + (r * 384 + 128 + blockIdx.x * 2 + (lane & 1)));
        const float c = __uint_as_float(lds32(sb + OFF_SC + r * 4));
        v[0] = fmaf(c, bf_lo(w.x), v[0]); v[1] = fmaf(c, bf_hi(w.x), v[1]); v[2] = fmaf(c, bf_lo(w.y), v[2]); v[3] = fmaf(c, bf_hi(w.y), v[3]);
        v[4] = fmaf(c, bf_lo(w.z), v[4]); v[5] = fmaf(c, bf_hi(w.z), v[5]); v[6] = fmaf(c, bf_lo(w.w), v[6]); v[7] = fmaf(c, bf_hi(w.w), v[7]);
      }
#pragma unroll
      for (int i = 0; i < 4; i++) { const bool up = lane & 16; v[i] = (up ? v[i+4] : v[i]) + __shfl_xor_sync(0xffffffff, up ? v[i] : v[i+4], 16); }
#pragma unroll
      for (int i = 0; i < 2; i++) { const bool up = lane & 8; v[i] = (up ? v[i+2] : v[i]) + __shfl_xor_sync(0xffffffff, up ? v[i] : v[i+2], 8); }
      { const bool up = lane & 4; v[0] = (up ? v[1] : v[0]) + __shfl_xor_sync(0xffffffff, up ? v[0] : v[1], 4); }
      v[0] += __shfl_xor_sync(0xffffffff, v[0], 2);
      const uint32_t epoch = lds32(sb + OFF_EPOCH);
      if (!(lane & 2)) publish_mod(scr->mod + blockIdx.x * 16 + (lane & 1) * 8 + ((lane >> 4) & 1) * 4 + ((lane >> 3) & 1) * 2 + ((lane >> 2) & 1), epoch, v[0]);
#pragma unroll 1
      for (int u = 0; u < 16; u++) {
        const int idx = u * 32 + lane;
        const uint4 wv = tagged_wait(scr->mod + idx * 4, (epoch + 1) & 0xffffu);
        stage_mod(sb, 2 + (idx >> 7), (idx & 127) * 4, bf_lo(wv.x), bf_lo(wv.y), bf_lo(wv.z), bf_lo(wv.w));
      }
      bar_arrive(BAR_AUX2, 160);
      bar_arrive(BAR_AUX2 + 1, 160);
    }
  } else {
    asm volatile("barrier.cluster.arrive.relaxed.aligned;" ::: "memory");
    asm volatile("setmaxnreg.inc.sync.aligned.u32 240;");
    const int cw = wg - 1;
    const int tid = threadIdx.x - 128, lane = threadIdx.x & 31, t4 = lane & 3;
    const uint32_t sbm = sb & 0x3FFFF;
    const uint32_t w = __shfl_sync(0xffffffff, threadIdx.x >> 5, 0) - 4;
    auto gaddr = [&](uint32_t index, uint32_t tmask) {
      uint32_t t_; asm volatile("mov.u32 %0, %%tid.x;" : "=r"(t_));
      return reinterpret_cast<uint4*>(reinterpret_cast<char*>(scr) + (size_t)((index + (t_ & tmask)) * 16u));
    };
    auto stash_at = [&](uint32_t i) { return gaddr(offsetof(Scratch, stash) / 16 + (blockIdx.x * STASH + i) * 256 - 128, 511); };
    auto mbox_at = [&](uint32_t i) { return gaddr(offsetof(Scratch, mbox) / 16 + ((rb * 2 + cw) * 24 + i) * 512, 127); };
    auto x1_at = [&](uint32_t i) { return gaddr(offsetof(Scratch, x1) / 16 + ((rb * 2 + cw) * 40 + i) * 128, 127); };
    uint32_t slot = 4;
    auto nxt = [&]() { const uint32_t s_ = slot; slot = (slot == NS - 1) ? 0 : slot + 1; return (sbm + s_ * SLOT) >> 4; };
    auto pp_enter = [&]() { bar_sync(BAR_PP + cw, 288); };
    auto pp_leave = [&]() { bar_arrive(BAR_PP + (cw ^ 1), 288); sched_fence(); };

    {
      const float c0 = bf_round(silu_f(__bfloat162float(cv0))), c1 = bf_round(silu_f(__bfloat162float(cv1)));
      if (tid == 0) sts32(sb + OFF_EPOCH, __uint_as_float(epoch0));
      const uint32_t x[4] = {wm0.x, wm0.y, wm0.z, wm0.w}, y[4] = {wm1.x, wm1.y, wm1.z, wm1.w};
      float v[8];
#pragma unroll
      for (int e = 0; e < 4; e++) { v[2*e] = fmaf(c0, bf_lo(x[e]), c1 * bf_lo(y[e])); v[2*e+1] = fmaf(c0, bf_hi(x[e]), c1 * bf_hi(y[e])); }
#pragma unroll
      for (int i = 0; i < 4; i++) { const bool up = lane & 16; v[i] = (up ? v[i+4] : v[i]) + __shfl_xor_sync(0xffffffff, up ? v[i] : v[i+4], 16); }
#pragma unroll
      for (int i = 0; i < 2; i++) { const bool up = lane & 8; v[i] = (up ? v[i+2] : v[i]) + __shfl_xor_sync(0xffffffff, up ? v[i] : v[i+2], 8); }
      asm volatile("st.shared.v2.f32 [%0], {%1, %2};" :: "r"(sb + OFF_RED + ((tid >> 5) * 64 + (lane & 7) * 8 + (lane >> 4) * 4 + ((lane >> 3) & 1) * 2) * 4), "f"(v[0]), "f"(v[1]) : "memory");
      bar_sync(BAR_CONS, 256);
      epoch0 = __shfl_sync(0xffffffff, lds32(sb + OFF_EPOCH), 0);
      if (tid < 64) {
        float s = 0.f;
#pragma unroll
        for (int i = 0; i < 8; i++) s += __uint_as_float(lds32(sb + OFF_RED + (i * 64 + tid) * 4));
        asm volatile("st.relaxed.gpu.global.u32 [%0], %1;" :: "l"(scr->part + (blockIdx.x >> 4) * 1024 + (blockIdx.x & 15) * 64 + tid),
                     "r"(((__float_as_uint(s) + 128u) & ~255u) | ((epoch0 + 1) & 255u)) : "memory");
      }
    }
    const uint32_t ep1 = epoch0 + 1;
    bar_sync(0, 384);
    asm volatile("barrier.cluster.wait.aligned;" ::: "memory");
    uint32_t a[128], act[56];
    if (cw == 1) bar_arrive(BAR_PP, 288);
    auto put_chunk = [&](const float (&d)[32], uint4* dst, int stride) {
#pragma unroll
      for (int i = 0; i < 4; i++)
        __stcg(dst + i * stride, make_uint4(pack_bf16(d[8*i], d[8*i+1]), pack_bf16(d[8*i+2], d[8*i+3]), pack_bf16(d[8*i+4], d[8*i+5]), pack_bf16(d[8*i+6], d[8*i+7])));
    };
    auto add_chunk = [&](float (&d)[32], const uint4* v) {
#pragma unroll
      for (int i = 0; i < 4; i++) {
        d[8*i] += bf_lo(v[i].x); d[8*i+1] += bf_hi(v[i].x); d[8*i+2] += bf_lo(v[i].y); d[8*i+3] += bf_hi(v[i].y);
        d[8*i+4] += bf_lo(v[i].z); d[8*i+5] += bf_hi(v[i].z); d[8*i+6] += bf_lo(v[i].w); d[8*i+7] += bf_hi(v[i].w);
      }
    };
    auto dsm_send = [&](const uint32_t (&pk)[16], int n) {
      const uint32_t slab = (n & 1) * 8 + w;
      uint32_t dst, bar;
      asm("mapa.shared::cluster.u32 %0, %1, %2;" : "=r"(dst) : "r"(sb + OFF_DSM + slab * 2048 + lane * 16), "r"(rank ^ 1));
      asm("mapa.shared::cluster.u32 %0, %1, %2;" : "=r"(bar) : "r"(bfull + 128 + slab * 8), "r"(rank ^ 1));
#pragma unroll
      for (int i = 0; i < 4; i++)
        asm volatile("st.async.weak.shared::cluster.mbarrier::complete_tx::bytes.v4.b32 [%0], {%1, %2, %3, %4}, [%5];"
          :: "r"(dst + i * 512), "r"(pk[4*i]), "r"(pk[4*i+1]), "r"(pk[4*i+2]), "r"(pk[4*i+3]), "r"(bar) : "memory");
      asm volatile("{\n.reg .pred p;\nsetp.eq.u32 p, %1, 0;\n@p mbarrier.arrive.expect_tx.shared::cta.b64 _, [%0], 2048;\n}" :: "r"(bfull + 128 + slab * 8), "r"(lane) : "memory");
    };
    auto dsm_probe = [&](int n) { return mbar_test(bfull + 128 + ((n & 1) * 8 + w) * 8, (n >> 1) & 1); };
    auto dsm_recv = [&](uint4 (&v)[4], int n, bool ready) {
      const uint32_t slab = (n & 1) * 8 + w;
      mbar_wait_warp(bfull + 128 + slab * 8, (n >> 1) & 1, ready);
#pragma unroll
      for (int i = 0; i < 4; i++)
        asm volatile("ld.shared.v4.u32 {%0,%1,%2,%3}, [%4];" : "=r"(v[i].x), "=r"(v[i].y), "=r"(v[i].z), "=r"(v[i].w) : "r"(sb + OFF_DSM + slab * 2048 + i * 512 + lane * 16) : "memory");
    };
    auto hint_at = [&](int kind, int owner) { return scr->cnt + ((kind * 16 + rb) * 8 + w) * 64 + owner * 8; };
    auto hint_post = [&](uint32_t* p) {
      asm volatile("{\n.reg .pred p;\nsetp.eq.u32 p, %1, 0;\n@p red.relaxed.gpu.global.add.u32 [%0], %2;\n}" :: "l"(p), "r"(lane), "r"(lane + 1) : "memory");
    };
    auto hint_peek = [&](const uint32_t* p) { uint32_t v; asm volatile("ld.relaxed.gpu.global.u32 %0, [%1];" : "=r"(v) : "l"(p) : "memory"); return v; };
    auto hint_wait = [&](const uint32_t* p, int n, uint32_t v) {
#pragma unroll 1
      for (int it = 0; it < MAX_POLL; it++) {
        if (__all_sync(0xffffffff, v == ep1 * n)) break;
        v = hint_peek(p);
      }
    };
#define LOAD_TAGGED(v, N, ADDR, tag)                                                         \
    _Pragma("unroll 1") for (int it = 0; it < MAX_POLL; it++) {                              \
      uint32_t x = 0;                                                                        \
      _Pragma("unroll") for (int i = 0; i < N; i++) x |= v[i].x ^ (tag);                     \
      if (!__any_sync(0xffffffff, x & 1u)) break;                                            \
      _Pragma("unroll") for (int i = 0; i < N; i++) v[i] = ld128(ADDR);                      \
    }
    auto splitk_out = [&](const uint32_t (&pk)[16], int c, int n0, uint32_t tag, bool ready) {
      if (!(c & 1)) dsm_send(pk, n0 + (c >> 1));
      else {
        uint4 u[4];
        uint4* dst = mbox_at(chunk_at(c) * 3 + (c >> 1));
        dsm_recv(u, n0 + (c >> 1), ready);
#pragma unroll
        for (int i = 0; i < 4; i++)
          st128(dst + i * 128, (hfma2(u[i].x, 0x3F803F80u, pk[4*i]) & ~1u) | tag, hfma2(u[i].y, 0x3F803F80u, pk[4*i+1]),
                hfma2(u[i].z, 0x3F803F80u, pk[4*i+2]), hfma2(u[i].w, 0x3F803F80u, pk[4*i+3]));
        hint_post(hint_at(tag ? CNT_O : CNT_D, chunk_at(c)));
      }
    };
    auto own_chunk = [&](float (&d)[32], int n, uint32_t tag, uint32_t hv, uint32_t gate) {
      uint4 v[12], r[4];
      const uint4* mp = mbox_at(hg * 3);
      hint_wait(hint_at(tag ? CNT_O : CNT_D, hg), 3, hv);
#pragma unroll
      for (int i = 0; i < 12; i++) v[i] = ld128(mp + i * 128);
      sched_fence();
      wg_wait<0>(); fence_regs(d);
      { uint4 u[4]; dsm_recv(u, n, false); add_chunk(d, u); }
      LOAD_TAGGED(v, 12, mp + i * 128, tag)
#pragma unroll
      for (int m = 0; m < 3; m++) add_chunk(d, v + 4 * m);
#pragma unroll
      for (int i = 0; i < 4; i++) {
        const float2 g0 = lds64(gate + hg * 256 + i * 64), g1 = lds64(gate + hg * 256 + i * 64 + 32);
        asm volatile("ld.shared.v4.u32 {%0,%1,%2,%3}, [%4];" : "=r"(r[i].x), "=r"(r[i].y), "=r"(r[i].z), "=r"(r[i].w) : "r"(sb + OFF_RES + i * 4096 + w * 512 + lane * 16) : "memory");
        d[8*i] = fmaf(d[8*i], g0.x, bf_lo(r[i].x)); d[8*i+1] = fmaf(d[8*i+1], g0.y, bf_hi(r[i].x));
        d[8*i+2] = fmaf(d[8*i+2], g0.x, bf_lo(r[i].y)); d[8*i+3] = fmaf(d[8*i+3], g0.y, bf_hi(r[i].y));
        d[8*i+4] = fmaf(d[8*i+4], g1.x, bf_lo(r[i].z)); d[8*i+5] = fmaf(d[8*i+5], g1.y, bf_hi(r[i].z));
        d[8*i+6] = fmaf(d[8*i+6], g1.x, bf_lo(r[i].w)); d[8*i+7] = fmaf(d[8*i+7], g1.y, bf_hi(r[i].w));
      }
    };
#pragma unroll 1
    for (int ph = 0; ; ph++) {
      if (ph == 0) {
        const uint32_t row = (tid >> 5) * 16 + (lane & 15);
        const uint32_t base = sb + row * 128, xr = row & 7, hi = lane >> 4;
        float cs[2][4] = {}, c0[2][4] = {}, c1[2][4] = {};
        uint4 pw[8];
        auto load_parts = [&]() {
#pragma unroll
          for (int i = 0; i < 8; i++)
            asm volatile("ld.relaxed.gpu.global.v4.u32 {%0,%1,%2,%3}, [%4];" : "=r"(pw[i].x), "=r"(pw[i].y), "=r"(pw[i].z), "=r"(pw[i].w) : "l"(scr->part + i * 1024 + tid * 4) : "memory");
        };
        auto stage_parts = [&]() {
#pragma unroll 1
          for (int tries = 0; ; tries++) {
            uint32_t bad = 0; const uint32_t tag = epoch0 + 1;
#pragma unroll
            for (int i = 0; i < 8; i++) bad |= (pw[i].x ^ tag) | (pw[i].y ^ tag) | (pw[i].z ^ tag) | (pw[i].w ^ tag);
            if (!(bad & 255u) || tries > 2000000) break;
            load_parts();
          }
          float v0 = 0.f, v1 = 0.f, v2 = 0.f, v3 = 0.f;
#pragma unroll
          for (int i = 0; i < 8; i++) {
            v0 += __uint_as_float(pw[i].x & ~255u); v1 += __uint_as_float(pw[i].y & ~255u);
            v2 += __uint_as_float(pw[i].z & ~255u); v3 += __uint_as_float(pw[i].w & ~255u);
          }
          stage_mod(sb, cw, (tid & 127) * 4, bf_round(v0), bf_round(v1), bf_round(v2), bf_round(v3));
        };
#pragma unroll
        for (int t = 0; t < 4; t++) {
          mbar_wait(bfull + t * 8, 0);
          if (t == 3) load_parts();
#pragma unroll
          for (int kk = 8*t; kk < 8*t + 8; kk++)
            ldsm4(base + (kk >> 2) * 16384 + (((((kk & 3) << 1) + hi) ^ xr) << 4), a[4*kk], a[4*kk+1], a[4*kk+2], a[4*kk+3]);
          if (t == 3) {
#pragma unroll
            for (int kk = 0; kk < 4; kk++) {
              uint4 x;
              ldsm4(base + hg * 16384 + ((((kk << 1) + hi) ^ xr) << 4), x.x, x.y, x.z, x.w);
              asm volatile("st.shared.v4.u32 [%0], {%1,%2,%3,%4};" :: "r"(sb + OFF_RES + kk * 4096 + w * 512 + lane * 16), "r"(x.x), "r"(x.y), "r"(x.z), "r"(x.w) : "memory");
            }
            fence_regs(a);
            bar_arrive(BAR_SOLO + cw, 160);
          }
          sched_fence();
#pragma unroll
          for (int kk = 8*t; kk < 8*t + 8; kk++) {
            hmma8(c0[0], a[4*kk], a[4*kk+1], a[4*kk]);
            hmma8(c1[0], a[4*kk], a[4*kk+1], a[4*kk+1]);
            hmma8(c0[1], a[4*kk+2], a[4*kk+3], a[4*kk+2]);
            hmma8(c1[1], a[4*kk+2], a[4*kk+3], a[4*kk+3]);
            hmma(cs[kk & 1], a[4*kk], a[4*kk+1], a[4*kk+2], a[4*kk+3], 0x3F803F80u, 0x3F803F80u);
            if (kk % 2 == 1) sched_fence();
            if (kk == 27) stage_parts();
          }
        }
        uint32_t lnc[4];
        const bool odd = lane & 4;
        const int src = (lane & ~3) | (lane >> 3);
        ln_coef(cs[0][0] + cs[1][0], __shfl_sync(0xffffffff, odd ? c0[0][1] + c0[1][1] : c0[0][0] + c0[1][0], src), lnc[0], lnc[1]);
        ln_coef(cs[0][2] + cs[1][2], __shfl_sync(0xffffffff, odd ? c1[0][3] + c1[1][3] : c1[0][2] + c1[1][2], src), lnc[2], lnc[3]);
        bar_sync(BAR_CONS, 256);
        if (blockIdx.x == 0 && tid == 0) asm volatile("st.relaxed.gpu.global.u32 [%0], %1;" :: "l"(&scr->epoch), "r"(epoch0 + 1) : "memory");
        ln_apply(a, lnc, sb + OFF_LN1 + t4 * 16, 0, 32);
      } else if (ph == 1) {
        bar_sync(BAR_AUX2 + cw, 160);
      }
      {
        float d[32], e[32];
#pragma unroll
        for (int i = 0; i < 32; i++) { d[i] = 0.f; e[i] = 0.f; }
        const int nch = ph == 2 ? 7 : 8;
        const uint32_t dhi = ph == 2 ? HI_SW64 : HI_SW128, kstep = ph == 2 ? 64 : 128;
        bool ready = false;
        uint32_t hv = 0;
        uint32_t lo_nx = nxt() | LBO_BOX;
        auto step = [&](int c, const int half) {
          const uint32_t lo = lo_nx;
          pp_enter();
          if (half == 0) ready = dsm_probe((c - 1) >> 1);
          else if (c == 7) hv = hint_peek(hint_at(CNT_O, hg));
          fence_regs(d);
#pragma unroll
          for (int i = 0; i < 64; i++) asm volatile("" : "+r"(a[64*half + i]) :: "memory");
          wg_fence();
#pragma unroll
          for (int k = 0; k < 16; k++)
            wgmma_n64<1>(d, a[64*half+4*k], a[64*half+4*k+1], a[64*half+4*k+2], a[64*half+4*k+3], desc_from(lo + k*kstep, dhi), half + k > 0);
          wg_commit();
          pp_leave();
          lo_nx = nxt() | LBO_BOX;
          asm volatile("" : "+r"(lo_nx));
        };
        auto epi_gu = [&](int c, const int half) {
          uint32_t r[4];
#pragma unroll
          for (int i = 0; i < 4; i++) r[i] = pack_bf16(silu_f(e[8*half+2*i]) * e[16+8*half+2*i], silu_f(e[8*half+2*i+1]) * e[16+8*half+2*i+1]);
          __stcg(stash_at(2*c + half), make_uint4(r[0], r[1], r[2], r[3]));
        };
        auto epilogue = [&](int c, const int half) {
          if (ph == 2) epi_gu(c, half);
          else if (half == 0) {
            if (ph == 0) put_chunk(e, stash_at(c * 4), 256);
            else {
              uint32_t pk[16];
#pragma unroll
              for (int i = 0; i < 16; i++) pk[i] = pack_bf16(e[2*i], e[2*i+1]);
              splitk_out(pk, c, 0, 1u, ready);
            }
          }
          sched_fence();
        };
#pragma unroll 1
        for (int c = 0; ; c++) {
          step(c, 0);
          if (c > 0) epilogue(c - 1, 0);
          wg_wait<0>(); fence_regs(d);
          step(c, 1);
          if (c > 0) epilogue(c - 1, 1);
          if (c == nch - 1) break;
          wg_wait<0>(); fence_regs(d);
#pragma unroll
          for (int i = 0; i < 32; i++) e[i] = d[i];
        }
        slot = slot == 0 ? NS - 1 : slot - 1;
        if (ph == 0) {
          uint32_t q[32];
          auto load_q = [&](int h) {
            const uint4* qp = stash_at(h * 8);
#pragma unroll
            for (int i = 0; i < 8; i++) { const uint4 v = __ldcg(qp + i * 256); q[4*i] = v.x; q[4*i+1] = v.y; q[4*i+2] = v.z; q[4*i+3] = v.w; }
          };
          load_q(0);
          sched_fence();
          wg_wait<0>(); fence_regs(d);
          put_chunk(d, stash_at(28), 256);
          if (cw == 0) bar_arrive(BAR_AUX, 160);
          const float C = QSCALE;
          const float OFS = (float)DELTA, BIG = __int_as_float((127 + 64 - DELTA) << 23);
          float o[64], s[64]; uint32_t p[32];
          float mc0 = 0.f, mc1 = 0.f;
          float l[4] = {0.f, 0.f, 0.f, 0.f};
          auto issue_qk = [&](uint32_t lo) {
            lo |= 1u << 16;
#pragma unroll
            for (int k = 0; k < 8; k++)
              wgmma_n128<0>(s, q[4*k], q[4*k+1], q[4*k+2], q[4*k+3], desc_from(lo + (k/4)*1024 + (k%4)*2, HI_SW128), k > 0);
            wg_commit();
          };
          auto issue_pv = [&](uint32_t lo, int accum) {
            lo |= LBO_BOX;
#pragma unroll
            for (int k = 0; k < 8; k++)
              wgmma_n128<1>(o, p[4*k], p[4*k+1], p[4*k+2], p[4*k+3], desc_from(lo + k*128, HI_SW128), k > 0 ? 1 : accum);
            wg_commit();
          };
          auto row_max = [&](float& x0, float& x1) {
            x0 = fmaxf(s[0], s[1]); x1 = fmaxf(s[2], s[3]);
#pragma unroll
            for (int j = 1; j < 16; j++) { x0 = fmaxf(x0, fmaxf(s[4*j], s[4*j+1])); x1 = fmaxf(x1, fmaxf(s[4*j+2], s[4*j+3])); }
            x0 = fmaxf(x0, __shfl_xor_sync(0xffffffff, x0, 1)); x1 = fmaxf(x1, __shfl_xor_sync(0xffffffff, x1, 1));
            x0 = fmaxf(x0, __shfl_xor_sync(0xffffffff, x0, 2)); x1 = fmaxf(x1, __shfl_xor_sync(0xffffffff, x1, 2));
            x0 = fmaf(x0, C, OFS); x1 = fmaf(x1, C, OFS);
          };
          auto e_fma = [&](int e) { asm volatile("fma.rn.f32 %0, %0, %1, %2;" : "+f"(s[e]) : "f"(C), "f"((e & 2) ? -mc1 : -mc0)); };
          auto e_ex2 = [&](int e) { asm volatile("ex2.approx.ftz.f32 %0, %0;" : "+f"(s[e])); };
          auto e_add = [&](int e) { asm volatile("add.f32 %0, %0, %1;" : "+f"(l[e & 3]) : "f"(s[e])); };
          auto e_cvt = [&](int c) { asm volatile("cvt.rn.bf16x2.f32 %0, %1, %2;" : "=r"(p[c]) : "f"(s[2*c+1]), "f"(s[2*c])); };
          auto inv_sums = [&](float pl0, float pl1, float& i0, float& i1) {
            pl0 += __shfl_xor_sync(0xffffffff, pl0, 1); pl1 += __shfl_xor_sync(0xffffffff, pl1, 1);
            pl0 += __shfl_xor_sync(0xffffffff, pl0, 2); pl1 += __shfl_xor_sync(0xffffffff, pl1, 2);
            i0 = rcp(pl0); i1 = rcp(pl1);
          };
          auto refresh = [&](uint32_t klo, int h, float pl0, float pl1) {
            float x0 = l[0] + l[1], x1 = l[2] + l[3];
            float f0, f1, g0, g1;
            if (__all_sync(0xffffffff, x0 + x1 < 3.0e38f)) {
              x0 = fmaxf(x0, __shfl_xor_sync(0xffffffff, x0, 1)); x1 = fmaxf(x1, __shfl_xor_sync(0xffffffff, x1, 1));
              x0 = fmaxf(x0, __shfl_xor_sync(0xffffffff, x0, 2)); x1 = fmaxf(x1, __shfl_xor_sync(0xffffffff, x1, 2));
              const int e0 = min(max(((__float_as_int(x0) >> 23) & 0xff) - 127 + DELTA, 0), 126), e1 = min(max(((__float_as_int(x1) >> 23) & 0xff) - 127 + DELTA, 0), 126);
              g0 = f0 = __int_as_float((127 - e0) << 23); g1 = f1 = __int_as_float((127 - e1) << 23);
              mc0 += (float)e0; mc1 += (float)e1;
              l[0] *= f0; l[1] *= f0; l[2] *= f1; l[3] *= f1;
            } else {
              const uint32_t kb = (sb & ~0x3FFFFu) + (klo << 4) + (lane & 7) * 128;
              const uint4* qs = stash_at(h * 8);
              float4* tmp = reinterpret_cast<float4*>(stash_at(32));
              x0 = -INFINITY; x1 = -INFINITY;
#pragma unroll 1
              for (int j = 0; j < 16; j++) {
                float c[4] = {0.f, 0.f, 0.f, 0.f};
#pragma unroll
                for (int k2 = 0; k2 < 4; k2++) {
                  uint32_t b0, b1, b2, b3;
                  const uint4 qa = __ldcg(qs + 2*k2 * 256), qb = __ldcg(qs + (2*k2 + 1) * 256);
                  ldsm4(kb + j * 1024 + (k2 >> 1) * 16384 + (((((k2 & 1) << 2) + (lane >> 3)) ^ (lane & 7)) << 4), b0, b1, b2, b3);
                  hmma(c, qa.x, qa.y, qa.z, qa.w, b0, b1);
                  hmma(c, qb.x, qb.y, qb.z, qb.w, b2, b3);
                }
                x0 = fmaxf(x0, fmaxf(c[0], c[1])); x1 = fmaxf(x1, fmaxf(c[2], c[3]));
                __stcg(tmp + j * 256, make_float4(c[0], c[1], c[2], c[3]));
              }
              x0 = fmaxf(x0, __shfl_xor_sync(0xffffffff, x0, 1)); x1 = fmaxf(x1, __shfl_xor_sync(0xffffffff, x1, 1));
              x0 = fmaxf(x0, __shfl_xor_sync(0xffffffff, x0, 2)); x1 = fmaxf(x1, __shfl_xor_sync(0xffffffff, x1, 2));
              x0 = fmaxf(fmaf(x0, C, OFS), mc0); x1 = fmaxf(fmaf(x1, C, OFS), mc1);
              f0 = ex2(mc0 - x0); f1 = ex2(mc1 - x1); g0 = g1 = 1.f;
              mc0 = x0; mc1 = x1;
              l[0] = pl0 * f0; l[1] = 0.f; l[2] = pl1 * f1; l[3] = 0.f;
#pragma unroll 1
              for (int j = 0; j < 16; j++) {
                float4 v = __ldcg(tmp + j * 256);
                v.x = ex2(fmaf(v.x, C, -mc0)); v.y = ex2(fmaf(v.y, C, -mc0)); v.z = ex2(fmaf(v.z, C, -mc1)); v.w = ex2(fmaf(v.w, C, -mc1));
                l[0] += v.x; l[1] += v.y; l[2] += v.z; l[3] += v.w;
                __stcg(tmp + j * 256, v);
              }
#pragma unroll
              for (int j = 0; j < 16; j++) { const float4 v = __ldcg(tmp + j * 256); s[4*j] = v.x; s[4*j+1] = v.y; s[4*j+2] = v.z; s[4*j+3] = v.w; }
            }
#pragma unroll
            for (int j = 0; j < 16; j++) {
              o[4*j] *= f0; o[4*j+1] *= f0; o[4*j+2] *= f1; o[4*j+3] *= f1;
              p[2*j] = pack_bf16(s[4*j] * g0, s[4*j+1] * g0); p[2*j+1] = pack_bf16(s[4*j+2] * g1, s[4*j+3] * g1);
            }
          };
          uint32_t klo, vlo, knx = 0, vnx = 0;
          float pl0 = 0.f, pl1 = 0.f;
          auto issue_both = [&](int accum) {
            klo = knx; vlo = vnx;
            pp_enter();
            fence_regs(q); fence_regs(s); fence_regs(o); fence_regs(p);
            wg_fence();
            issue_qk(klo);
            issue_pv(vlo, accum);
            pp_leave();
          };
          auto softmax = [&](const bool FIRST, int h) {
            wg_wait<1>();
            fence_regs(s); fence_regs(q);
            pl0 = l[0] + l[1]; pl1 = l[2] + l[3];
            if (FIRST) { row_max(mc0, mc1); l[0] = l[1] = l[2] = l[3] = 0.f; }
            constexpr int LF = 2, LA = 4, SP = 32;
            e_fma(0); e_fma(1);
            int cvt_done = 0;
            float i0 = 0.f, i1 = 0.f;
#pragma unroll
            for (int e = 0; e < 64; e++) {
              if (e % 2 == 0) sched_fence();
              if (!FIRST && e == 4 && h > 0) load_q(h & 3);
              if (FIRST && e == 8) inv_sums(pl0, pl1, i0, i1);
              if (e == 2) { knx = nxt(); vnx = nxt(); asm volatile("" : "+r"(knx), "+r"(vnx)); }
              if (e == SP) {
                wg_wait<0>();
                fence_regs(o); fence_regs(p);
                if (FIRST && h > 0) {
                  uint4* op = stash_at((h - 1) * 8);
#pragma unroll
                  for (int i = 0; i < 8; i++)
                    __stcg(op + i * 256, make_uint4(pack_bf16(o[8*i] * i0, o[8*i+1] * i0), pack_bf16(o[8*i+2] * i1, o[8*i+3] * i1),
                                                    pack_bf16(o[8*i+4] * i0, o[8*i+5] * i0), pack_bf16(o[8*i+6] * i1, o[8*i+7] * i1)));
                }
              }
              e_ex2(e);
              if (e + LF < 64) e_fma(e + LF);
              if (e >= LA) e_add(e - LA);
              if (e >= SP) {
                int target = (e - SP + 1) * 32 / (64 - SP); const int lim = (e - LA + 1) / 2; if (target > lim) target = lim;
#pragma unroll
                for (int c = 0; c < 32; c++) if (c >= cvt_done && c < target) e_cvt(c);
                cvt_done = target > cvt_done ? target : cvt_done;
              }
            }
#pragma unroll
            for (int e = 64 - LA; e < 64; e++) e_add(e);
#pragma unroll
            for (int c = 0; c < 32; c++) if (c >= cvt_done) e_cvt(c);
          };
#pragma unroll
          for (int i = 0; i < 64; i++) { o[i] = 0.f; s[i] = 0.f; }
#pragma unroll
          for (int i = 0; i < 32; i++) p[i] = 0u;
          klo = nxt(); vlo = klo;
          pp_enter();
          fence_regs(q); fence_regs(s); fence_regs(o); fence_regs(p);
          wg_fence();
          issue_qk(klo);
          wg_commit();
          pp_leave();
#pragma unroll 1
          for (int h = 0; ; h++) {
            softmax(true, h);
            pl0 = pl1 = 0.f;
            int j = 0;
            auto stale = [&]() { return __any_sync(0xffffffff, !(fmaxf(l[0] + l[1], l[2] + l[3]) < BIG)); };
            bool bad = stale();
#pragma unroll 1
            for (;;) {
              if (bad) { refresh(klo, h, pl0, pl1); if (j == 15) break; }
#pragma unroll 1
              do {
                issue_both(j != 0);
                j++;
                softmax(false, j == 15 ? h + 1 : 0);
                bad = stale();
              } while (!bad && j != 15);
              if (!bad) break;
            }
            if (h == 3) break;
            issue_both(1);
          }
          {
            vlo = knx; slot = slot == 0 ? NS - 1 : slot - 1;
            pp_enter();
            fence_regs(o); fence_regs(p);
            wg_fence();
            issue_pv(vlo, 1);
            pp_leave();
            const uint4* sp = stash_at(0);
#pragma unroll
            for (int i = 8; i < 24; i++) { const uint4 v = __ldcg(sp + i * 256); a[4*i] = v.x; a[4*i+1] = v.y; a[4*i+2] = v.z; a[4*i+3] = v.w; }
#pragma unroll
            for (int i = 0; i < 32; i++) a[i] = q[i];
            float i0, i1; inv_sums(l[0] + l[1], l[2] + l[3], i0, i1);
            sched_fence();
            wg_wait<0>();
            fence_regs(o);
#pragma unroll
            for (int i = 0; i < 32; i++) a[96 + i] = pack_bf16(o[2*i] * ((i & 1) ? i1 : i0), o[2*i+1] * ((i & 1) ? i1 : i0));
          }
        } else if (ph == 2) {
          const uint4* sp = stash_at(0);
#pragma unroll
          for (int i = 0; i < 12; i++) { const uint4 v = __ldcg(sp + i * 256); act[4*i] = v.x; act[4*i+1] = v.y; act[4*i+2] = v.z; act[4*i+3] = v.w; }
          sched_fence();
          wg_wait<0>(); fence_regs(d);
#pragma unroll
          for (int i = 0; i < 8; i++) act[48 + i] = pack_bf16(silu_f(d[2*i]) * d[16+2*i], silu_f(d[2*i+1]) * d[16+2*i+1]);
          break;
        } else {
          own_chunk(d, 3, 1u, hv, sb + OFF_GA + t4 * 8);
          const uint32_t par = ep1 & 1;
          float4 st = {0.f, 0.f, 0.f, 0.f};
          {
            uint4* dst = x1_at(hg * 5);
#pragma unroll
            for (int i = 0; i < 4; i++)
              st128(dst + i * 128, pack_bf16(__uint_as_float(((__float_as_uint(d[8*i]) + 0x10000u) & 0xFFFE0000u) | (par << 16)), d[8*i+1]),
                    pack_bf16(d[8*i+2], d[8*i+3]), pack_bf16(d[8*i+4], d[8*i+5]), pack_bf16(d[8*i+6], d[8*i+7]));
#pragma unroll
            for (int j = 0; j < 8; j++) {
              st.x += d[4*j] + d[4*j+1]; st.y = fmaf(d[4*j], d[4*j], fmaf(d[4*j+1], d[4*j+1], st.y));
              st.z += d[4*j+2] + d[4*j+3]; st.w = fmaf(d[4*j+2], d[4*j+2], fmaf(d[4*j+3], d[4*j+3], st.w));
            }
#pragma unroll
            for (int m = 1; m <= 2; m++) {
              st.x += __shfl_xor_sync(0xffffffff, st.x, m); st.y += __shfl_xor_sync(0xffffffff, st.y, m);
              st.z += __shfl_xor_sync(0xffffffff, st.z, m); st.w += __shfl_xor_sync(0xffffffff, st.w, m);
            }
            if (t4 == 0) st128(dst + 4 * 128 - lane + (lane >> 2), (__float_as_uint(st.x) & ~1u) | par, __float_as_uint(st.y), __float_as_uint(st.z), __float_as_uint(st.w));
            hint_post(hint_at(CNT_X, 0));
          }
#pragma unroll
          for (int i = 0; i < 4; i++)
            asm volatile("st.shared.v4.u32 [%0], {%1,%2,%3,%4};" :: "r"(sb + OFF_RES + i * 4096 + w * 512 + lane * 16), "r"(pack_bf16(d[8*i], d[8*i+1])),
                         "r"(pack_bf16(d[8*i+2], d[8*i+3])), "r"(pack_bf16(d[8*i+4], d[8*i+5])), "r"(pack_bf16(d[8*i+6], d[8*i+7])) : "memory");
          hint_wait(hint_at(CNT_X, 0), 8, hint_peek(hint_at(CNT_X, 0)));
          const uint4* xp = x1_at(0);
          const uint4* sp = xp - lane + (lane >> 2);
          uint4 sv[8], xv[4][8];
#pragma unroll
          for (int m = 0; m < 8; m++) sv[m] = ld128(sp + (5 * m + 4) * 128);
#pragma unroll
          for (int kk = 0; kk < 16; kk++) {
            if (kk % 8 == 0) sched_fence();
            xv[kk >> 3][kk & 7] = ld128(xp + ((kk >> 2) * 5 + (kk & 3)) * 128);
          }
          sched_fence();
          LOAD_TAGGED(sv, 8, sp + (5 * i + 4) * 128, par)
          st = make_float4(0.f, 0.f, 0.f, 0.f);
#pragma unroll
          for (int m = 0; m < 8; m++) { st.x += __uint_as_float(sv[m].x & ~1u); st.y += __uint_as_float(sv[m].y); st.z += __uint_as_float(sv[m].z); st.w += __uint_as_float(sv[m].w); }
          uint32_t lnc[4];
          ln_coef(st.x, st.y, lnc[0], lnc[1]); ln_coef(st.z, st.w, lnc[2], lnc[3]);
#pragma unroll
          for (int g = 0; g < 4; g++) {
            LOAD_TAGGED(xv[g], 8, xp + ((2 * g + (i >> 2)) * 5 + (i & 3)) * 128, par)
#pragma unroll
            for (int u = 0; u < 8; u++) { a[32*g+4*u] = xv[g][u].x & ~1u; a[32*g+4*u+1] = xv[g][u].y; a[32*g+4*u+2] = xv[g][u].z; a[32*g+4*u+3] = xv[g][u].w; }
            if (g < 2) {
#pragma unroll
              for (int u = 0; u < 8; u++) xv[(g + 2) & 3][u] = ld128(xp + ((2 * (g + 2) + (u >> 2)) * 5 + (u & 3)) * 128);
            }
            ln_apply(a, lnc, sb + OFF_LN2 + t4 * 16, 8 * g, 8 * g + 8);
          }
        }
      }
    }
    {
      float d[32]; uint32_t pk[16], hv = 0, lo_nx = nxt() | LBO_BOX;
#pragma unroll
      for (int i = 0; i < 32; i++) d[i] = 0.f;
#pragma unroll
      for (int i = 0; i < 16; i++) pk[i] = 0;
#pragma unroll 1
      for (int c = 0; ; c++) {
        const uint32_t lo = lo_nx;
        pp_enter();
        const bool ready = dsm_probe(4 + ((c - 1) >> 1));
        if (c == 7) hv = hint_peek(hint_at(CNT_D, hg));
        fence_regs(d); fence_regs(act);
        wg_fence();
#pragma unroll
        for (int k = 0; k < 14; k++)
          wgmma_n64<1>(d, act[4*k], act[4*k+1], act[4*k+2], act[4*k+3], desc_from(lo + (k/7)*1024 + (k%7)*128, HI_SW128), k > 0);
        wg_commit();
        if (c < 7 || cw == 0) bar_arrive(BAR_PP + (cw ^ 1), 288);
        sched_fence();
        lo_nx = nxt() | LBO_BOX;
        asm volatile("" : "+r"(lo_nx));
        if (c > 0) splitk_out(pk, c - 1, 4, 0u, ready);
        if (c == 7) break;
        sched_fence();
        wg_wait<0>(); fence_regs(d);
#pragma unroll
        for (int i = 0; i < 16; i++) pk[i] = pack_bf16(d[2*i], d[2*i+1]);
      }
      own_chunk(d, 7, 0u, hv, sb + OFF_GB + t4 * 8);
      uint32_t u[2][8];
#pragma unroll
      for (int j = 0; j < 8; j++) { u[0][j] = pack_bf16(d[4*j], d[4*j+1]); u[1][j] = pack_bf16(d[4*j+2], d[4*j+3]); }
#pragma unroll
      for (int r = 0; r < 2; r++) {
#pragma unroll
        for (int i = 0; i < 4; i++) {
          const bool hi = t4 & 2;
          const uint32_t x = __shfl_xor_sync(0xffffffff, hi ? u[r][i] : u[r][i + 4], 2);
          if (hi) u[r][i] = x; else u[r][i + 4] = x;
        }
#pragma unroll
        for (int i = 0; i < 4; i++) {
          const int k = (i & 1) + (i >> 1) * 4;
          const bool hi = t4 & 1;
          const uint32_t x = __shfl_xor_sync(0xffffffff, hi ? u[r][k] : u[r][k + 2], 1);
          if (hi) u[r][k] = x; else u[r][k + 2] = x;
        }
        uint4* op = reinterpret_cast<uint4*>(out) + (size_t)(rb * 128 + w * 16 + (lane >> 2) + r * 8) * 64 + hg * 8 + t4 * 2;
        op[0] = make_uint4(u[r][0], u[r][2], u[r][4], u[r][6]);
        op[1] = make_uint4(u[r][1], u[r][3], u[r][5], u[r][7]);
      }
    }
  }
}

typedef CUresult (*EncodeFn)(CUtensorMap*, CUtensorMapDataType, cuuint32_t, void*, const cuuint64_t*, const cuuint64_t*, const cuuint32_t*,
                             const cuuint32_t*, CUtensorMapInterleave, CUtensorMapSwizzle, CUtensorMapL2promotion, CUtensorMapFloatOOBfill);

void make_map(EncodeFn enc, CUtensorMap* m, const void* ptr, uint64_t rows, uint64_t cols, uint32_t box_rows, uint32_t box_cols, CUtensorMapSwizzle sw) {
  cuuint64_t dims[2] = {cols, rows};
  cuuint64_t strides[1] = {cols * 2};
  cuuint32_t box[2] = {box_cols, box_rows};
  cuuint32_t es[2] = {1, 1};
  enc(m, CU_TENSOR_MAP_DATA_TYPE_BFLOAT16, 2, const_cast<void*>(ptr), dims, strides, box, es, CU_TENSOR_MAP_INTERLEAVE_NONE, sw,
      CU_TENSOR_MAP_L2_PROMOTION_L2_128B, CU_TENSOR_MAP_FLOAT_OOB_FILL_NONE);
}

}

extern "C" void kernel_launch(void* const* d_in, const int* in_sizes, int n_in, void* d_out, int out_size) {
  (void)in_sizes; (void)n_in; (void)out_size;
  static EncodeFn enc = nullptr;
  static Scratch* scr = nullptr;
  if (!enc) {
    void* fn = nullptr; cudaDriverEntryPointQueryResult qr;
    cudaGetDriverEntryPoint("cuTensorMapEncodeTiled", &fn, cudaEnableDefault, &qr);
    enc = (EncodeFn)fn;
    cudaGetSymbolAddress((void**)&scr, g_scratch);
    cudaFuncSetAttribute(block_kernel, cudaFuncAttributeMaxDynamicSharedMemorySize, SMEM_BYTES);
  }
  Maps maps;
  const CUtensorMapSwizzle S128 = CU_TENSOR_MAP_SWIZZLE_128B, S64 = CU_TENSOR_MAP_SWIZZLE_64B;
  make_map(enc, &maps.x, d_in[0], 2048, 512, 128, 64, S128);
  make_map(enc, &maps.k, d_in[1], 16384, 128, 128, 64, S128);
  make_map(enc, &maps.v, d_in[2], 16384, 128, 128, 64, S128);
  make_map(enc, &maps.wq, d_in[3], 512, 4096, 128, 64, S128);
  make_map(enc, &maps.wo, d_in[4], 4096, 512, 128, 64, S128);
  make_map(enc, &maps.wg, d_in[6], 512, 1792, 256, 32, S64);
  make_map(enc, &maps.wu, d_in[7], 512, 1792, 256, 32, S64);
  make_map(enc, &maps.wd, d_in[8], 1792, 512, 112, 64, S128);
  block_kernel<<<128, 384, SMEM_BYTES, cudaStreamPerThread>>>((const __nv_bfloat16*)d_in[9], (const uint4*)d_in[10], scr, (uint32_t*)d_out, maps);
}
```
